```python
import torch

def _softmax(x, axis=-1):
    return torch.softmax(x, dim=axis)

def _gelu(x):
    return torch.nn.functional.gelu(x, approximate='tanh')

def _silu(x):
    return torch.nn.functional.silu(x)

def _sigmoid(x):
    return torch.sigmoid(x)

def _layernorm(x, axis=-1, eps=1e-05):
    m = x.mean(dim=axis, keepdim=True)
    v = x.var(dim=axis, keepdim=True, unbiased=False)
    return (x - m) / torch.sqrt(v + eps)

def _scatter_add(tgt, idx, src, axis=0):
    return tgt.clone().index_add_(axis, idx, src)

def _segment_sum(src, seg, n):
    out = torch.zeros((n,) + src.shape[1:], dtype=src.dtype)
    return out.index_add_(0, seg, src)

def _pad(x, pw):
    flat = tuple((v for pair in reversed(pw) for v in pair))
    return torch.nn.functional.pad(x, flat)
kernel_name = 'adaLN_cond__ssm_conv_s4__mixer_gmlp__prompt'

def setup_inputs():

    _w = lambda a: (lambda t: t.to(torch.bfloat16) if t.is_floating_point() else t)(torch.as_tensor(a))

    def _A_setup():
        B, L, D, N = (1, 2048, 448, 256)
        A_re = -(lambda _x: torch.exp(torch.as_tensor(_x)))((lambda *s: torch.randn(*s, dtype=torch.bfloat16) * 3.2)(D, N))
        A_im = torch.pi * (lambda *s: torch.randn(*s, dtype=torch.bfloat16) * 0.1)(D, N)
        B_re = (lambda *s: torch.randn(*s, dtype=torch.bfloat16) * 0.2)(D, N)
        B_im = (lambda *s: torch.randn(*s, dtype=torch.bfloat16) * 0.2)(D, N)
        C_re = (lambda *s: torch.randn(*s, dtype=torch.bfloat16) * 0.1)(D, N)
        C_im = (lambda *s: torch.randn(*s, dtype=torch.bfloat16) * 0.2)(D, N)
        log_dt = (lambda *s: torch.randn(*s, dtype=torch.bfloat16) * 0.1)(D) * 0.5 - 4.0
        Dskip = (lambda *s: torch.randn(*s, dtype=torch.bfloat16) * 0.1)(D)
        return {'u': _w((lambda *s: torch.randn(*s, dtype=torch.bfloat16) * 0.05)(B, L, D)), 'A_re': _w(A_re), 'A_im': _w(A_im), 'B_re': _w(B_re), 'B_im': _w(B_im), 'C_re': _w(C_re), 'C_im': _w(C_im), 'log_dt': _w(log_dt), 'Dskip': _w(Dskip)}
    _A_in = _A_setup()

    def _B_setup():
        B, S, D, F = (1, 2048, 448, 1792)
        Fh = F // 2
        return {'x': _w((lambda *s: torch.randn(*s, dtype=torch.bfloat16) * 0.05)(B, S, D)), 'w_in': _w((lambda *s: torch.randn(*s, dtype=torch.bfloat16) * 0.4)(D, 2 * Fh)), 'w_sp': _w(0.01 * (lambda *s: torch.randn(*s, dtype=torch.bfloat16) * 0.4)(S, S)), 'b_sp': _w(1.0 + 0.01 * (lambda *s: torch.randn(*s, dtype=torch.bfloat16) * 0.05)(S)), 'w_out': _w((lambda *s: torch.randn(*s, dtype=torch.bfloat16) * 0.05)(Fh, D))}
    _B_in = _B_setup()
    return {'A_u': _A_in['u'], 'A_A_re': _A_in['A_re'], 'A_A_im': _A_in['A_im'], 'A_B_re': _A_in['B_re'], 'A_B_im': _A_in['B_im'], 'A_C_re': _A_in['C_re'], 'A_C_im': _A_in['C_im'], 'A_log_dt': _A_in['log_dt'], 'A_Dskip': _A_in['Dskip'], 'B_x': _B_in['x'], 'B_w_in': _B_in['w_in'], 'B_w_sp': _B_in['w_sp'], 'B_b_sp': _B_in['b_sp'], 'B_w_out': _B_in['w_out'], 'c': _w((lambda *s: torch.randn(*s, dtype=torch.bfloat16) * 0.2)(1, 448) * 8.0), 'w_mod': _w((lambda *s: torch.randn(*s, dtype=torch.bfloat16) * 0.2)(448, 6 * 448) * 448 ** (-0.5) * 8.0)}

def reference(A_u, A_A_re, A_A_im, A_B_re, A_B_im, A_C_re, A_C_im, A_log_dt, A_Dskip, B_x, B_w_in, B_w_sp, B_b_sp, B_w_out, c, w_mod):

    def _A_ref(u, A_re, A_im, B_re, B_im, C_re, C_im, log_dt, Dskip):
        Bsz, L, D = u.shape
        dt = torch.exp(log_dt)[:, None]
        A = A_re + 1j * A_im
        Bc = B_re + 1j * B_im
        Cc = C_re + 1j * C_im
        logdA = dt * A
        dB = dt * Bc
        l = (lambda x, dt: x.to(dt))(torch.arange(L), A_re.dtype)
        P = torch.exp(logdA[:, :, None] * l[None, None, :])
        K = torch.einsum('dn,dnl,dn->dl', Cc, P, dB).real
        L2 = 2 * L
        Kp = _pad(K, ((0, 0), (0, L)))
        up = (lambda x, *d: x.permute(*d))(u, 0, 2, 1)
        up = _pad(up, ((0, 0), (0, 0), (0, L)))
        Kf = (lambda x, axes=(-2, -1): torch.fft.rfft2(x.float(), dim=axes))(Kp[:, None, :], axes=(-2, -1))
        Uf = (lambda x, axes=(-2, -1): torch.fft.rfft2(x.float(), dim=axes))(up[:, :, None, :], axes=(-2, -1))
        Yf = Uf * Kf[None, :, :, :]
        y = (lambda x, s, axes=(-2, -1): torch.fft.irfft2(x, s=s, dim=axes).to(torch.bfloat16))(Yf, (1, L2), axes=(-2, -1))[:, :, 0, :L]
        y = (lambda x, *d: x.permute(*d))(y, 0, 2, 1) + u * Dskip[None, None, :]
        return y

    def _B_ref(x, w_in, w_sp, b_sp, w_out):
        B, S, D = x.shape
        F = w_in.shape[-1]
        Fh = F // 2
        z = _gelu(torch.einsum('bsd,df->bsf', x, w_in))
        z1 = z[..., :Fh].clone()
        z2 = _layernorm(z[..., Fh:], axis=-1)
        g = torch.einsum('ts,bsf->btf', w_sp, z2) + b_sp[None, :, None]
        return torch.einsum('bsf,fd->bsd', z1 * g, w_out)
    x = A_u
    mod = (_silu(c) @ w_mod).reshape(c.shape[0], 6, 1, -1)
    sa, ca, ga, sb, cb, gb = (mod[:, 0].clone(), mod[:, 1].clone(), mod[:, 2].clone(), mod[:, 3].clone(), mod[:, 4].clone(), mod[:, 5].clone())
    h = _layernorm(x, axis=-1) * (1 + ca) + sa
    x = x + ga * _A_ref(h, A_A_re, A_A_im, A_B_re, A_B_im, A_C_re, A_C_im, A_log_dt, A_Dskip)
    h = _layernorm(x, axis=-1) * (1 + cb) + sb
    x = x + gb * _B_ref(h, B_w_in, B_w_sp, B_b_sp, B_w_out)
    return x
```

```cpp
#include <cuda_runtime.h>
#include <cuda.h>
#include <cuda_bf16.h>
#include <stdint.h>

typedef __nv_bfloat16 bf16;
typedef __nv_bfloat162 bf162;

constexpr int L_ = 2048, D_ = 448, NM_ = 256, F_ = 1792, FH_ = 896;

__device__ __align__(16) uint2 g_stat1[L_];
__device__ __align__(16) uint2 g_stat2[L_];
__device__ __align__(128) uint4 g_uT[112 * 1024];
__device__ uint32_t g_mod[6 * D_];
__device__ __align__(1024) bf16 g_x1T[D_ * L_];
__device__ __align__(1024) uint8_t g_wimg[16 * 7 * 14336];
__device__ __align__(1024) uint8_t g_waug[16 * 3584];
__device__ __align__(1024) uint8_t g_woimg[4 * 8 * 25088];
__device__ __align__(16) uint2 g_zstat[L_ * 8];
__device__ unsigned int g_zcnt[16 * 32];
__device__ __align__(1024) uint8_t g_z2img[32 * 4 * 28672];
__device__ __align__(1024) uint8_t g_pimg[32 * 8 * 14336];
__device__ unsigned int g_epoch;

__device__ __forceinline__ uint32_t smem_u32(const void* p) { return (uint32_t)__cvta_generic_to_shared(p); }
__device__ __forceinline__ void mbar_init(uint32_t bar, uint32_t cnt) { asm volatile("mbarrier.init.shared::cta.b64 [%0], %1;" ::"r"(bar), "r"(cnt) : "memory"); }
__device__ __forceinline__ void mbar_expect_tx(uint32_t bar, uint32_t bytes) { asm volatile("mbarrier.arrive.expect_tx.shared::cta.b64 _, [%0], %1;" ::"r"(bar), "r"(bytes) : "memory"); }
__device__ __forceinline__ void mbar_arrive(uint32_t bar) { asm volatile("mbarrier.arrive.shared::cta.b64 _, [%0];" ::"r"(bar) : "memory"); }
__device__ __forceinline__ uint32_t mapa(uint32_t addr, uint32_t cta) { uint32_t r; asm volatile("mapa.shared::cluster.u32 %0, %1, %2;" : "=r"(r) : "r"(addr), "r"(cta)); return r; }
__device__ __forceinline__ void mbar_arrive_remote(uint32_t raddr) { asm volatile("mbarrier.arrive.shared::cluster.b64 _, [%0];" ::"r"(raddr) : "memory"); }
__device__ __forceinline__ void mbar_wait(uint32_t bar, uint32_t parity) {
  uint32_t done; uint32_t it = 0;
  do {
    asm volatile("{\n.reg .pred p;\nmbarrier.try_wait.parity.shared::cta.b64 p, [%1], %2;\nselp.u32 %0, 1, 0, p;\n}\n" : "=r"(done) : "r"(bar), "r"(parity) : "memory");
    if (!done && ++it > (1u << 22)) __trap();
  } while (!done);
}
__device__ __forceinline__ void tma_load_2d(uint32_t dst, const void* tmap, int c0, int c1, uint32_t bar) {
  asm volatile("cp.async.bulk.tensor.2d.shared::cluster.global.mbarrier::complete_tx::bytes [%0], [%1, {%3, %4}], [%2];" ::"r"(dst), "l"(tmap), "r"(bar), "r"(c0), "r"(c1) : "memory");
}
__device__ __forceinline__ void tma_load_3d(uint32_t dst, const void* tmap, int c0, int c1, int c2, uint32_t bar) {
  asm volatile("cp.async.bulk.tensor.3d.shared::cluster.global.mbarrier::complete_tx::bytes [%0], [%1, {%3, %4, %5}], [%2];" ::"r"(dst), "l"(tmap), "r"(bar), "r"(c0), "r"(c1), "r"(c2) : "memory");
}
__device__ __forceinline__ void tma_load_2d_mc(uint32_t dst, const void* tmap, int c0, int c1, uint32_t bar, uint16_t mask) {
  asm volatile("cp.async.bulk.tensor.2d.shared::cluster.global.mbarrier::complete_tx::bytes.multicast::cluster [%0], [%1, {%3, %4}], [%2], %5;" ::"r"(dst), "l"(tmap), "r"(bar), "r"(c0), "r"(c1), "h"(mask) : "memory");
}
__device__ __forceinline__ void tmap_prefetch(const void* tmap) { asm volatile("prefetch.tensormap [%0];" ::"l"(tmap) : "memory"); }
__device__ __forceinline__ void tma_store_2d(const void* tmap, uint32_t src, int c0, int c1) {
  asm volatile("cp.async.bulk.tensor.2d.global.shared::cta.bulk_group [%0, {%2, %3}], [%1];" ::"l"(tmap), "r"(src), "r"(c0), "r"(c1) : "memory");
}
__device__ __forceinline__ void bulk_load(uint32_t dst, const void* src, uint32_t bytes, uint32_t bar) {
  asm volatile("cp.async.bulk.shared::cluster.global.mbarrier::complete_tx::bytes [%0], [%1], %2, [%3];" ::"r"(dst), "l"(src), "r"(bytes), "r"(bar) : "memory");
}
__device__ __forceinline__ void bulk_store(void* dst, uint32_t src, uint32_t bytes) {
  asm volatile("cp.async.bulk.global.shared::cta.bulk_group [%0], [%1], %2;" ::"l"(dst), "r"(src), "r"(bytes) : "memory");
}
__device__ __forceinline__ void l2_prefetch(const void* p, uint32_t bytes) { asm volatile("cp.async.bulk.prefetch.L2.global [%0], %1;" ::"l"(p), "r"(bytes) : "memory"); }
__device__ __forceinline__ void bulk_commit() { asm volatile("cp.async.bulk.commit_group;" ::: "memory"); }
__device__ __forceinline__ void bulk_wait_all() { asm volatile("cp.async.bulk.wait_group 0;" ::: "memory"); }
__device__ __forceinline__ void bulk_wait_read() { asm volatile("cp.async.bulk.wait_group.read 0;" ::: "memory"); }
__device__ __forceinline__ void fence_async_smem() { asm volatile("fence.proxy.async.shared::cta;" ::: "memory"); }
__device__ __forceinline__ void wg_fence() { asm volatile("wgmma.fence.sync.aligned;" ::: "memory"); }
__device__ __forceinline__ void wg_commit() { asm volatile("wgmma.commit_group.sync.aligned;" ::: "memory"); }
template <int N> __device__ __forceinline__ void wg_wait() { asm volatile("wgmma.wait_group.sync.aligned %0;" ::"n"(N) : "memory"); }
template <int N> __device__ __forceinline__ void fence_regs(float* d) {
#pragma unroll
  for (int i = 0; i < N; i++) asm volatile("" : "+f"(d[i])::"memory");
}
__device__ __forceinline__ void bar_sync(int id, int n) { asm volatile("bar.sync %0, %1;" ::"r"(id), "r"(n) : "memory"); }
__device__ __forceinline__ void bar_arrive(int id, int n) { asm volatile("bar.arrive %0, %1;" ::"r"(id), "r"(n) : "memory"); }
__device__ __forceinline__ void pdl_wait() { asm volatile("griddepcontrol.wait;" ::: "memory"); }
__device__ __forceinline__ void pdl_launch() { asm volatile("griddepcontrol.launch_dependents;" ::: "memory"); }
__device__ __forceinline__ constexpr uint64_t desc_hi(uint32_t lbo, uint32_t sbo, uint32_t swz) {
  return ((uint64_t)(lbo >> 4) << 16) | ((uint64_t)(sbo >> 4) << 32) | ((uint64_t)swz << 62);
}
__device__ __forceinline__ uint64_t mkdesc(uint32_t addr, uint64_t hi) { return hi | (uint64_t)((addr & 0x3FFFFu) >> 4); }
__device__ __forceinline__ uint32_t pack_bf16(float lo, float hi) { uint32_t r; asm("cvt.rn.bf16x2.f32 %0, %1, %2;" : "=r"(r) : "f"(hi), "f"(lo)); return r; }
__device__ __forceinline__ float bf_lo(uint32_t v) { return __uint_as_float(v << 16); }
__device__ __forceinline__ float bf_hi(uint32_t v) { return __uint_as_float(v & 0xFFFF0000u); }
__device__ __forceinline__ float bf_round(float x) { return __bfloat162float(__float2bfloat16_rn(x)); }
__device__ __forceinline__ uint32_t hmul2(uint32_t a, uint32_t b) { uint32_t r; asm("mul.rn.bf16x2 %0, %1, %2;" : "=r"(r) : "r"(a), "r"(b)); return r; }
__device__ __forceinline__ uint32_t hadd2(uint32_t a, uint32_t b) { uint32_t r; asm("add.rn.bf16x2 %0, %1, %2;" : "=r"(r) : "r"(a), "r"(b)); return r; }
__device__ __forceinline__ uint32_t hsub2(uint32_t a, uint32_t b) { uint32_t r; asm("sub.rn.bf16x2 %0, %1, %2;" : "=r"(r) : "r"(a), "r"(b)); return r; }
__device__ __forceinline__ uint32_t prmt(uint32_t a, uint32_t b, uint32_t s) { uint32_t r; asm("prmt.b32 %0, %1, %2, %3;" : "=r"(r) : "r"(a), "r"(b), "r"(s)); return r; }
__device__ __forceinline__ uint4 lds128(uint32_t a) { uint4 v; asm volatile("ld.shared.v4.u32 {%0,%1,%2,%3}, [%4];" : "=r"(v.x), "=r"(v.y), "=r"(v.z), "=r"(v.w) : "r"(a) : "memory"); return v; }
__device__ __forceinline__ float4 lds128f(uint32_t a) { float4 v; asm volatile("ld.shared.v4.f32 {%0,%1,%2,%3}, [%4];" : "=f"(v.x), "=f"(v.y), "=f"(v.z), "=f"(v.w) : "r"(a) : "memory"); return v; }
__device__ __forceinline__ uint2 lds64(uint32_t a) { uint2 v; asm volatile("ld.shared.v2.u32 {%0,%1}, [%2];" : "=r"(v.x), "=r"(v.y) : "r"(a) : "memory"); return v; }
__device__ __forceinline__ float2 lds64f(uint32_t a) { float2 v; asm volatile("ld.shared.v2.f32 {%0,%1}, [%2];" : "=f"(v.x), "=f"(v.y) : "r"(a) : "memory"); return v; }
__device__ __forceinline__ uint32_t lds32(uint32_t a) { uint32_t v; asm volatile("ld.shared.u32 %0, [%1];" : "=r"(v) : "r"(a) : "memory"); return v; }
__device__ __forceinline__ float lds32f(uint32_t a) { float v; asm volatile("ld.shared.f32 %0, [%1];" : "=f"(v) : "r"(a) : "memory"); return v; }
__device__ __forceinline__ uint32_t lds16(uint32_t a) { uint16_t v; asm volatile("ld.shared.u16 %0, [%1];" : "=h"(v) : "r"(a) : "memory"); return v; }
__device__ __forceinline__ void sts128(uint32_t a, uint4 v) { asm volatile("st.shared.v4.u32 [%0], {%1,%2,%3,%4};" ::"r"(a), "r"(v.x), "r"(v.y), "r"(v.z), "r"(v.w) : "memory"); }
__device__ __forceinline__ void sts64(uint32_t a, uint32_t x, uint32_t y) { asm volatile("st.shared.v2.u32 [%0], {%1,%2};" ::"r"(a), "r"(x), "r"(y) : "memory"); }
__device__ __forceinline__ void sts64f(uint32_t a, float x, float y) { asm volatile("st.shared.v2.f32 [%0], {%1,%2};" ::"r"(a), "f"(x), "f"(y) : "memory"); }
__device__ __forceinline__ void sts32(uint32_t a, uint32_t x) { asm volatile("st.shared.u32 [%0], %1;" ::"r"(a), "r"(x) : "memory"); }
__device__ __forceinline__ void sts16(uint32_t a, uint32_t x) { asm volatile("st.shared.u16 [%0], %1;" ::"r"(a), "h"((uint16_t)x) : "memory"); }
__device__ __forceinline__ void sts32f(uint32_t a, float x) { asm volatile("st.shared.f32 [%0], %1;" ::"r"(a), "f"(x) : "memory"); }
__device__ __forceinline__ void ldsm4(uint32_t a, uint32_t& r0, uint32_t& r1, uint32_t& r2, uint32_t& r3) {
  asm volatile("ldmatrix.sync.aligned.m8n8.x4.shared.b16 {%0,%1,%2,%3}, [%4];" : "=r"(r0), "=r"(r1), "=r"(r2), "=r"(r3) : "r"(a) : "memory");
}
__device__ __forceinline__ void ldsm4t(uint32_t a, uint32_t& r0, uint32_t& r1, uint32_t& r2, uint32_t& r3) {
  asm volatile("ldmatrix.sync.aligned.m8n8.x4.trans.shared.b16 {%0,%1,%2,%3}, [%4];" : "=r"(r0), "=r"(r1), "=r"(r2), "=r"(r3) : "r"(a) : "memory");
}
__device__ __forceinline__ void stsm4(uint32_t a, uint32_t r0, uint32_t r1, uint32_t r2, uint32_t r3) {
  asm volatile("stmatrix.sync.aligned.m8n8.x4.shared.b16 [%0], {%1,%2,%3,%4};" ::"r"(a), "r"(r0), "r"(r1), "r"(r2), "r"(r3) : "memory");
}
__device__ __forceinline__ void stsm4t(uint32_t a, uint32_t r0, uint32_t r1, uint32_t r2, uint32_t r3) {
  asm volatile("stmatrix.sync.aligned.m8n8.x4.trans.shared.b16 [%0], {%1,%2,%3,%4};" ::"r"(a), "r"(r0), "r"(r1), "r"(r2), "r"(r3) : "memory");
}
__device__ __forceinline__ void mma16816(float* c, uint32_t a0, uint32_t a1, uint32_t a2, uint32_t a3, uint32_t b0, uint32_t b1) {
  asm volatile("mma.sync.aligned.m16n8k16.row.col.f32.bf16.bf16.f32 {%0,%1,%2,%3}, {%4,%5,%6,%7}, {%8,%9}, {%0,%1,%2,%3};"
               : "+f"(c[0]), "+f"(c[1]), "+f"(c[2]), "+f"(c[3]) : "r"(a0), "r"(a1), "r"(a2), "r"(a3), "r"(b0), "r"(b1));
}
__device__ __forceinline__ uint4 ldg128_nc(const void* p) { uint4 v; asm volatile("ld.global.nc.L1::no_allocate.v4.u32 {%0,%1,%2,%3}, [%4];" : "=r"(v.x), "=r"(v.y), "=r"(v.z), "=r"(v.w) : "l"(p)); return v; }
__device__ __forceinline__ uint2 ldg64_nc(const void* p) { uint2 v; asm volatile("ld.global.nc.L1::no_allocate.v2.u32 {%0,%1}, [%2];" : "=r"(v.x), "=r"(v.y) : "l"(p)); return v; }
__device__ __forceinline__ uint32_t ldg32_nc(const void* p) { uint32_t v; asm volatile("ld.global.nc.u32 %0, [%1];" : "=r"(v) : "l"(p)); return v; }
__device__ __forceinline__ uint32_t ldg16_nc(const void* p) { uint16_t v; asm volatile("ld.global.nc.u16 %0, [%1];" : "=h"(v) : "l"(p)); return v; }
__device__ __forceinline__ uint4 ldg128_cg(const void* p) { uint4 v; asm volatile("ld.global.cg.v4.u32 {%0,%1,%2,%3}, [%4];" : "=r"(v.x), "=r"(v.y), "=r"(v.z), "=r"(v.w) : "l"(p) : "memory"); return v; }
__device__ __forceinline__ void st_rlx64x(void* p, uint32_t x, uint32_t y) { asm volatile("st.relaxed.gpu.global.b64 [%0], %1;" ::"l"(p), "l"((uint64_t)x | ((uint64_t)y << 32)) : "memory"); }
__device__ __forceinline__ void st_rlx32(void* p, uint32_t x) { asm volatile("st.relaxed.gpu.global.u32 [%0], %1;" ::"l"(p), "r"(x) : "memory"); }
__device__ __forceinline__ uint32_t ld_rlx32(const void* p) { uint32_t v; asm volatile("ld.relaxed.gpu.global.u32 %0, [%1];" : "=r"(v) : "l"(p) : "memory"); return v; }
__device__ __forceinline__ uint2 ld_acq64(const void* p) {
  uint64_t a; asm volatile("ld.acquire.gpu.global.b64 %0, [%1];" : "=l"(a) : "l"(p) : "memory");
  return make_uint2((uint32_t)a, (uint32_t)(a >> 32));
}
__device__ __forceinline__ uint4 ld_rlx2x64(const void* p) {
  uint64_t a, b; asm volatile("ld.relaxed.gpu.global.v2.b64 {%0,%1}, [%2];" : "=l"(a), "=l"(b) : "l"(p) : "memory");
  return make_uint4((uint32_t)a, (uint32_t)(a >> 32), (uint32_t)b, (uint32_t)(b >> 32));
}
__device__ __forceinline__ float ln_den(float var) { return bf_round(sqrtf(bf_round(bf_round(var) + 1e-5f))); }
__device__ __forceinline__ float ln_rden(float var) { return 1.0f / ln_den(var); }
#define PT(k, role, i)
__device__ __forceinline__ void wgmma_rs_n16(float* d, uint32_t a0, uint32_t a1, uint32_t a2, uint32_t a3, uint64_t db, int sc){
  asm volatile("{\n.reg .pred p;\nsetp.ne.b32 p, %13, 0;\nwgmma.mma_async.sync.aligned.m64n16k16.f32.bf16.bf16 {%0,%1,%2,%3,%4,%5,%6,%7}, {%8,%9,%10,%11}, %12, p, 1, 1, 0;\n}\n"
   : "+f"(d[0]),"+f"(d[1]),"+f"(d[2]),"+f"(d[3]),"+f"(d[4]),"+f"(d[5]),"+f"(d[6]),"+f"(d[7]) : "r"(a0), "r"(a1), "r"(a2), "r"(a3), "l"(db), "r"(sc));
}
__device__ __forceinline__ void wgmma_rs_n24(float* d, uint32_t a0, uint32_t a1, uint32_t a2, uint32_t a3, uint64_t db, int sc){
  asm volatile("{\n.reg .pred p;\nsetp.ne.b32 p, %17, 0;\nwgmma.mma_async.sync.aligned.m64n24k16.f32.bf16.bf16 {%0,%1,%2,%3,%4,%5,%6,%7,%8,%9,%10,%11}, {%12,%13,%14,%15}, %16, p, 1, 1, 0;\n}\n"
   : "+f"(d[0]),"+f"(d[1]),"+f"(d[2]),"+f"(d[3]),"+f"(d[4]),"+f"(d[5]),"+f"(d[6]),"+f"(d[7]),"+f"(d[8]),"+f"(d[9]),"+f"(d[10]),"+f"(d[11]) : "r"(a0), "r"(a1), "r"(a2), "r"(a3), "l"(db), "r"(sc));
}
__device__ __forceinline__ void wgmma_rs_n32(float* d, uint32_t a0, uint32_t a1, uint32_t a2, uint32_t a3, uint64_t db, int sc){
  asm volatile("{\n.reg .pred p;\nsetp.ne.b32 p, %21, 0;\nwgmma.mma_async.sync.aligned.m64n32k16.f32.bf16.bf16 {%0,%1,%2,%3,%4,%5,%6,%7,%8,%9,%10,%11,%12,%13,%14,%15}, {%16,%17,%18,%19}, %20, p, 1, 1, 0;\n}\n"
   : "+f"(d[0]),"+f"(d[1]),"+f"(d[2]),"+f"(d[3]),"+f"(d[4]),"+f"(d[5]),"+f"(d[6]),"+f"(d[7]),"+f"(d[8]),"+f"(d[9]),"+f"(d[10]),"+f"(d[11]),"+f"(d[12]),"+f"(d[13]),"+f"(d[14]),"+f"(d[15]) : "r"(a0), "r"(a1), "r"(a2), "r"(a3), "l"(db), "r"(sc));
}
__device__ __forceinline__ void wgmma_rs_n112_tb(float* d, uint32_t a0, uint32_t a1, uint32_t a2, uint32_t a3, uint64_t db, int sc){
  asm volatile("{\n.reg .pred p;\nsetp.ne.b32 p, %61, 0;\nwgmma.mma_async.sync.aligned.m64n112k16.f32.bf16.bf16 {%0,%1,%2,%3,%4,%5,%6,%7,%8,%9,%10,%11,%12,%13,%14,%15,%16,%17,%18,%19,%20,%21,%22,%23,%24,%25,%26,%27,%28,%29,%30,%31,%32,%33,%34,%35,%36,%37,%38,%39,%40,%41,%42,%43,%44,%45,%46,%47,%48,%49,%50,%51,%52,%53,%54,%55}, {%56,%57,%58,%59}, %60, p, 1, 1, 1;\n}\n"
   : "+f"(d[0]),"+f"(d[1]),"+f"(d[2]),"+f"(d[3]),"+f"(d[4]),"+f"(d[5]),"+f"(d[6]),"+f"(d[7]),"+f"(d[8]),"+f"(d[9]),"+f"(d[10]),"+f"(d[11]),"+f"(d[12]),"+f"(d[13]),"+f"(d[14]),"+f"(d[15]),"+f"(d[16]),"+f"(d[17]),"+f"(d[18]),"+f"(d[19]),"+f"(d[20]),"+f"(d[21]),"+f"(d[22]),"+f"(d[23]),"+f"(d[24]),"+f"(d[25]),"+f"(d[26]),"+f"(d[27]),"+f"(d[28]),"+f"(d[29]),"+f"(d[30]),"+f"(d[31]),"+f"(d[32]),"+f"(d[33]),"+f"(d[34]),"+f"(d[35]),"+f"(d[36]),"+f"(d[37]),"+f"(d[38]),"+f"(d[39]),"+f"(d[40]),"+f"(d[41]),"+f"(d[42]),"+f"(d[43]),"+f"(d[44]),"+f"(d[45]),"+f"(d[46]),"+f"(d[47]),"+f"(d[48]),"+f"(d[49]),"+f"(d[50]),"+f"(d[51]),"+f"(d[52]),"+f"(d[53]),"+f"(d[54]),"+f"(d[55]) : "r"(a0), "r"(a1), "r"(a2), "r"(a3), "l"(db), "r"(sc));
}
template<int TA,int TB> __device__ __forceinline__ void wgmma_ss_n112(float* d, uint64_t da, uint64_t db, int sc){
  asm volatile("{\n.reg .pred p;\nsetp.ne.b32 p, %58, 0;\nwgmma.mma_async.sync.aligned.m64n112k16.f32.bf16.bf16 {%0,%1,%2,%3,%4,%5,%6,%7,%8,%9,%10,%11,%12,%13,%14,%15,%16,%17,%18,%19,%20,%21,%22,%23,%24,%25,%26,%27,%28,%29,%30,%31,%32,%33,%34,%35,%36,%37,%38,%39,%40,%41,%42,%43,%44,%45,%46,%47,%48,%49,%50,%51,%52,%53,%54,%55}, %56, %57, p, 1, 1, %59, %60;\n}\n"
   : "+f"(d[0]),"+f"(d[1]),"+f"(d[2]),"+f"(d[3]),"+f"(d[4]),"+f"(d[5]),"+f"(d[6]),"+f"(d[7]),"+f"(d[8]),"+f"(d[9]),"+f"(d[10]),"+f"(d[11]),"+f"(d[12]),"+f"(d[13]),"+f"(d[14]),"+f"(d[15]),"+f"(d[16]),"+f"(d[17]),"+f"(d[18]),"+f"(d[19]),"+f"(d[20]),"+f"(d[21]),"+f"(d[22]),"+f"(d[23]),"+f"(d[24]),"+f"(d[25]),"+f"(d[26]),"+f"(d[27]),"+f"(d[28]),"+f"(d[29]),"+f"(d[30]),"+f"(d[31]),"+f"(d[32]),"+f"(d[33]),"+f"(d[34]),"+f"(d[35]),"+f"(d[36]),"+f"(d[37]),"+f"(d[38]),"+f"(d[39]),"+f"(d[40]),"+f"(d[41]),"+f"(d[42]),"+f"(d[43]),"+f"(d[44]),"+f"(d[45]),"+f"(d[46]),"+f"(d[47]),"+f"(d[48]),"+f"(d[49]),"+f"(d[50]),"+f"(d[51]),"+f"(d[52]),"+f"(d[53]),"+f"(d[54]),"+f"(d[55]) : "l"(da), "l"(db), "r"(sc), "n"(TA), "n"(TB));
}
template<int TA,int TB> __device__ __forceinline__ void wgmma_ss_n224(float* d, uint64_t da, uint64_t db, int sc){
  asm volatile("{\n.reg .pred p;\nsetp.ne.b32 p, %114, 0;\nwgmma.mma_async.sync.aligned.m64n224k16.f32.bf16.bf16 {%0,%1,%2,%3,%4,%5,%6,%7,%8,%9,%10,%11,%12,%13,%14,%15,%16,%17,%18,%19,%20,%21,%22,%23,%24,%25,%26,%27,%28,%29,%30,%31,%32,%33,%34,%35,%36,%37,%38,%39,%40,%41,%42,%43,%44,%45,%46,%47,%48,%49,%50,%51,%52,%53,%54,%55,%56,%57,%58,%59,%60,%61,%62,%63,%64,%65,%66,%67,%68,%69,%70,%71,%72,%73,%74,%75,%76,%77,%78,%79,%80,%81,%82,%83,%84,%85,%86,%87,%88,%89,%90,%91,%92,%93,%94,%95,%96,%97,%98,%99,%100,%101,%102,%103,%104,%105,%106,%107,%108,%109,%110,%111}, %112, %113, p, 1, 1, %115, %116;\n}\n"
   : "+f"(d[0]),"+f"(d[1]),"+f"(d[2]),"+f"(d[3]),"+f"(d[4]),"+f"(d[5]),"+f"(d[6]),"+f"(d[7]),"+f"(d[8]),"+f"(d[9]),"+f"(d[10]),"+f"(d[11]),"+f"(d[12]),"+f"(d[13]),"+f"(d[14]),"+f"(d[15]),"+f"(d[16]),"+f"(d[17]),"+f"(d[18]),"+f"(d[19]),"+f"(d[20]),"+f"(d[21]),"+f"(d[22]),"+f"(d[23]),"+f"(d[24]),"+f"(d[25]),"+f"(d[26]),"+f"(d[27]),"+f"(d[28]),"+f"(d[29]),"+f"(d[30]),"+f"(d[31]),"+f"(d[32]),"+f"(d[33]),"+f"(d[34]),"+f"(d[35]),"+f"(d[36]),"+f"(d[37]),"+f"(d[38]),"+f"(d[39]),"+f"(d[40]),"+f"(d[41]),"+f"(d[42]),"+f"(d[43]),"+f"(d[44]),"+f"(d[45]),"+f"(d[46]),"+f"(d[47]),"+f"(d[48]),"+f"(d[49]),"+f"(d[50]),"+f"(d[51]),"+f"(d[52]),"+f"(d[53]),"+f"(d[54]),"+f"(d[55]),"+f"(d[56]),"+f"(d[57]),"+f"(d[58]),"+f"(d[59]),"+f"(d[60]),"+f"(d[61]),"+f"(d[62]),"+f"(d[63]),"+f"(d[64]),"+f"(d[65]),"+f"(d[66]),"+f"(d[67]),"+f"(d[68]),"+f"(d[69]),"+f"(d[70]),"+f"(d[71]),"+f"(d[72]),"+f"(d[73]),"+f"(d[74]),"+f"(d[75]),"+f"(d[76]),"+f"(d[77]),"+f"(d[78]),"+f"(d[79]),"+f"(d[80]),"+f"(d[81]),"+f"(d[82]),"+f"(d[83]),"+f"(d[84]),"+f"(d[85]),"+f"(d[86]),"+f"(d[87]),"+f"(d[88]),"+f"(d[89]),"+f"(d[90]),"+f"(d[91]),"+f"(d[92]),"+f"(d[93]),"+f"(d[94]),"+f"(d[95]),"+f"(d[96]),"+f"(d[97]),"+f"(d[98]),"+f"(d[99]),"+f"(d[100]),"+f"(d[101]),"+f"(d[102]),"+f"(d[103]),"+f"(d[104]),"+f"(d[105]),"+f"(d[106]),"+f"(d[107]),"+f"(d[108]),"+f"(d[109]),"+f"(d[110]),"+f"(d[111]) : "l"(da), "l"(db), "r"(sc), "n"(TA), "n"(TB));
}

struct KMap { uint32_t v[640]; };
constexpr int kv_ij(int i, int j) { return i * 40 + j; }
constexpr int KV_ZERO = 39;
constexpr int kv_entry(int v) {
  return v < 256 ? kv_ij(v % 8, v / 8)
       : v < 512 ? kv_ij(8 + (v % 8) / 2, (v - 256) / 8)
       : v < 1024 ? kv_ij(12 + 2 * ((v - 512) / 256) + (v % 8) / 4, ((v - 512) % 256) / 8)
       : v < 2048 ? kv_ij(16 + (v - 1024) / 256, ((v - 1024) % 256) / 8)
       : kv_ij(20, 0);
}
constexpr int round_pos(int x) {
  int step = x < 256 ? 1 : x < 512 ? 2 : 4;
  int q = x / step, r = x % step;
  if (step > 1 && (2 * r > step || (2 * r == step && (q & 1)))) q++;
  return q * step;
}
constexpr int z_entry(int z) {
  if (z < 592) { int x = z - 63; return (x >= 0 && x <= 514) ? kv_entry(round_pos(x)) : KV_ZERO; }
  if (z < 720) { int a = z - 592 - 62; return (a >= 1 && a <= 63) ? kv_entry(512 + 8 * a) : KV_ZERO; }
  if (z < 848) { int a = z - 720 - 63; return (a >= 0 && a <= 63) ? kv_entry(516 + 8 * a) : KV_ZERO; }
  int a = z - 848 - 62; return (a >= 1 && a <= 128) ? kv_entry(1024 + 8 * a) : KV_ZERO;
}
constexpr KMap make_kmap() {
  KMap m{};
  for (int w = 0; w < 640; w++) m.v[w] = (uint32_t)z_entry(2 * w) | ((uint32_t)z_entry(2 * w + 1) << 10) | ((uint32_t)z_entry(2 * w + 2) << 20);
  return m;
}
__device__ const KMap g_kmap = make_kmap();

constexpr int K1_R = 0, K1_RSZ = 28672, K1_Z0 = 0, K1_Z1 = 2624, K1_Y0 = 5248, K1_Y2 = K1_Y0 + 8768;
constexpr int K1_H = 114688, K1_HSZ = 5248, K1_CS = 656;
constexpr int K1_S = 135680, K1_SSZ = 11520, K1_S5 = 0, K1_S3 = 3456, K1_EO = 6912;
constexpr int K1_U = K1_S + 4 * K1_SSZ, K1_KV = K1_U + 16384, K1_KVSZ = 1920, K1_MISC = K1_KV + 4 * K1_KVSZ;
constexpr int K1_AUXX = 19456, K1_AUXY = K1_AUXX + 100352;
constexpr int K1_SMEM = K1_AUXY + 100352;
static_assert(K1_SMEM >= K1_MISC + 256, "");

struct cplx { float r, i; };
__device__ __forceinline__ cplx cmul(cplx a, cplx b) { cplx c; c.r = fmaf(a.r, b.r, -a.i * b.i); c.i = fmaf(a.r, b.i, a.i * b.r); return c; }
__device__ __forceinline__ cplx csq(cplx a) { cplx c; c.r = fmaf(a.r, a.r, -a.i * a.i); c.i = (a.r + a.r) * a.i; return c; }
__device__ __forceinline__ cplx cexp_p(float ar, float ai, float p) {
  float m; asm("ex2.approx.ftz.f32 %0, %1;" : "=f"(m) : "f"(ar * p * 1.4426950408889634f));
  float t = ai * p * 0.15915494309189535f;
  t = (t - rintf(t)) * 6.283185307179586f;
  cplx c; c.r = m * __cosf(t); c.i = m * __sinf(t); return c;
}
__device__ __forceinline__ uint32_t h_chunk(uint32_t hb, int q) { return hb + (7 - (q & 7)) * K1_CS + ((q >> 3) + 9) * 16; }
__device__ __forceinline__ int ypad(int l) { return l + 8 * (l >> 7) + 4 * ((((l >> 5) & 3) + 1) >> 1); }
__device__ __forceinline__ void unpack_rev(uint4 v, float* o) {
  o[7] = bf_lo(v.x); o[6] = bf_hi(v.x); o[5] = bf_lo(v.y); o[4] = bf_hi(v.y);
  o[3] = bf_lo(v.z); o[2] = bf_hi(v.z); o[1] = bf_lo(v.w); o[0] = bf_hi(v.w);
}

struct K1Args {
  const bf16 *u, *Are, *Aim, *Bre, *Bim, *Cre, *Cim, *logdt, *dskip, *w_out, *c, *w_sp, *w_mod, *w_in;
};

__device__ __forceinline__ void ln1_stage(uint4 ur0, uint4 ur1, uint32_t stage, int warp, int lane) {
  if (lane < 28) { sts128(stage + warp * 912 + lane * 32, ur0); sts128(stage + warp * 912 + lane * 32 + 16, ur1); }
  __syncthreads();
}
__device__ __forceinline__ void ln1_rows(uint4 ur0, uint4 ur1, uint32_t stage, int tid, int warp, int lane, int cta, uint32_t tag) {
  {
    const int rp = tid & 7, cg = tid >> 3;
    const uint2 a0 = lds64(stage + (2 * rp) * 912 + cg * 8), a1 = lds64(stage + (2 * rp + 1) * 912 + cg * 8);
    uint2 b0, b1;
    if (cg < 48) { b0 = lds64(stage + (2 * rp) * 912 + (cg + 64) * 8); b1 = lds64(stage + (2 * rp + 1) * 912 + (cg + 64) * 8); }
    g_uT[cg * 1024 + cta * 8 + rp] = make_uint4(a0.x, a0.y, a1.x, a1.y);
    if (cg < 48) g_uT[(cg + 64) * 1024 + cta * 8 + rp] = make_uint4(b0.x, b0.y, b1.x, b1.y);
  }
  float x[16];
  x[0] = bf_lo(ur0.x); x[1] = bf_hi(ur0.x); x[2] = bf_lo(ur0.y); x[3] = bf_hi(ur0.y); x[4] = bf_lo(ur0.z); x[5] = bf_hi(ur0.z); x[6] = bf_lo(ur0.w); x[7] = bf_hi(ur0.w);
  x[8] = bf_lo(ur1.x); x[9] = bf_hi(ur1.x); x[10] = bf_lo(ur1.y); x[11] = bf_hi(ur1.y); x[12] = bf_lo(ur1.z); x[13] = bf_hi(ur1.z); x[14] = bf_lo(ur1.w); x[15] = bf_hi(ur1.w);
  float s = (((x[0] + x[1]) + (x[2] + x[3])) + ((x[4] + x[5]) + (x[6] + x[7]))) + (((x[8] + x[9]) + (x[10] + x[11])) + ((x[12] + x[13]) + (x[14] + x[15])));
#pragma unroll
  for (int o = 16; o; o >>= 1) s += __shfl_xor_sync(~0u, s, o);
  const float mean = s * (1.0f / D_);
  float q0 = 0.f, q1 = 0.f;
#pragma unroll
  for (int i = 0; i < 8; i++) { const float da = x[i] - mean, db = x[8 + i] - mean; q0 = fmaf(da, da, q0); q1 = fmaf(db, db, q1); }
  float q = lane < 28 ? q0 + q1 : 0.f;
#pragma unroll
  for (int o = 16; o; o >>= 1) q += __shfl_xor_sync(~0u, q, o);
  if (lane == 0) sts64(stage + 16 * 912 + warp * 8, __float_as_uint(bf_round(mean)) | tag, __float_as_uint(ln_rden(q * (1.0f / D_))));
  if (warp != 15) { __syncwarp(); bar_arrive(1, 512); }
  else {
    bar_sync(1, 512);
    const uint2 v = lds64(stage + 16 * 912 + (lane & 15) * 8);
    asm volatile("fence.acq_rel.gpu;" ::: "memory");
    if (lane < 16) st_rlx64x(&g_stat1[cta * 16 + lane], v.x, v.y);
    __syncwarp();
  }
}

template <int NT, bool TWO>
__device__ __forceinline__ void aux_gemv(uint32_t slab, const float* v0, const float* v1, float* red, int warp, int lane) {
  float acc[NT][4];
#pragma unroll
  for (int n = 0; n < NT; n++) acc[n][0] = acc[n][1] = acc[n][2] = acc[n][3] = 0.f;
#pragma unroll
  for (int i = 0; i < 2; i++) {
    const int ks = warp + 16 * i;
    if (ks < 28) {
      uint32_t a0 = 0, a1 = 0, a2 = 0, a3 = 0;
      if (lane < 4) {
        const float* p = v0 + ks * 16 + 2 * lane; a0 = pack_bf16(p[0], p[1]); a2 = pack_bf16(p[8], p[9]);
        if (TWO) { const float* q = v1 + ks * 16 + 2 * lane; a1 = pack_bf16(q[0], q[1]); a3 = pack_bf16(q[8], q[9]); }
      }
      const uint32_t base = slab + (ks * 16 + (lane & 15)) * (NT * 16) + (lane >> 4) * 16;
#pragma unroll
      for (int n2 = 0; n2 < (NT + 1) / 2; n2++) {
        uint32_t b0, b1, b2, b3;
        ldsm4t(base + n2 * 32, b0, b1, b2, b3);
        mma16816(acc[2 * n2], a0, a1, a2, a3, b0, b1);
        if (2 * n2 + 1 < NT) mma16816(acc[2 * n2 + 1], a0, a1, a2, a3, b2, b3);
      }
    }
  }
  if (lane < 4) {
#pragma unroll
    for (int n = 0; n < NT; n++) {
      *(float2*)(red + warp * 224 + n * 8 + 2 * lane) = make_float2(acc[n][0], acc[n][1]);
      if (TWO) *(float2*)(red + warp * 224 + 112 + n * 8 + 2 * lane) = make_float2(acc[n][2], acc[n][3]);
    }
  }
}
__device__ __forceinline__ float aux_sum16(const float* red, int i) {
  float s = 0.f;
#pragma unroll
  for (int r = 0; r < 16; r++) s += red[r * 224 + i];
  return s;
}

__device__ __forceinline__ void k1_aux(const K1Args& a, const CUtensorMap* tm_wmod1, const CUtensorMap* tm_wmod2, const CUtensorMap* tm_win, uint8_t* smem_raw,
                                       int tid, int warp, int lane, int cta, uint32_t tagraw) {
  const uint32_t sm = smem_u32(smem_raw), bar = sm + 3840;
  const int ax = cta - 112;
  uint4 ur0 = make_uint4(0, 0, 0, 0), ur1 = ur0;
  if (lane < 28) { const bf16* p = a.u + (cta * 16 + warp) * D_ + lane * 16; ur0 = ldg128_nc(p); ur1 = ldg128_nc(p + 8); }
  uint32_t craw = 0;
  if (tid < D_) craw = ldg16_nc(a.c + tid);
  if (tid == 0) {
    mbar_init(bar, 1); mbar_init(bar + 8, 1); mbar_init(bar + 16, 1);
    asm volatile("fence.mbarrier_init.release.cluster;" ::: "memory");
    tmap_prefetch(tm_wmod1); tmap_prefetch(tm_wmod2); tmap_prefetch(tm_win);
  }
  ln1_stage(ur0, ur1, sm + 4096, warp, lane);
  const int c1 = ((ax >> 2) == 3 ? 4 : (ax >> 2)) * D_ + (ax & 3) * 112;
  const int c2 = ((ax >> 3) ? 5 : 3) * D_ + (ax & 7) * 56;
  if (tid == 0) {
    mbar_expect_tx(bar, 448 * 224);
    tma_load_2d(sm + K1_AUXY, tm_wmod2, c1, 0, bar);
    tma_load_2d(sm + K1_AUXY + 224 * 224, tm_wmod2, c1, 224, bar);
    mbar_expect_tx(bar + 16, 448 * 224);
    tma_load_2d(sm + K1_AUXX, tm_win, ax * 112, 0, bar + 16);
    tma_load_2d(sm + K1_AUXX + 224 * 224, tm_win, ax * 112, 224, bar + 16);
  }
  if (tid == 64) l2_prefetch((const uint8_t*)a.w_mod + cta * 18816, 18816);
  const uint32_t tag = (tagraw + 1u) & 0xFFFFu;
  float* sv = (float*)smem_raw;
  float* red = (float*)(smem_raw + 4096);
  if (tid < D_) { const float c = bf_lo(craw); sv[tid] = bf_round(c / (1.0f + expf(-c))); }
  ln1_rows(ur0, ur1, sm + 4096, tid, warp, lane, cta, tag);
  PT(0, warp >> 2, 1);
  __syncthreads();
  mbar_wait(bar, 0);
  PT(0, warp >> 2, 3);
  aux_gemv<14, false>(sm + K1_AUXY, sv, sv, red, warp, lane);
  __syncthreads();
  if (tid == 0) {
    mbar_expect_tx(bar + 8, 448 * 112);
    tma_load_2d(sm + K1_AUXY, tm_wmod1, c2, 0, bar + 8);
    tma_load_2d(sm + K1_AUXY + 224 * 112, tm_wmod1, c2, 224, bar + 8);
  }
  if (tid < 112) st_rlx32(&g_mod[c1 + tid], __float_as_uint(bf_round(aux_sum16(red, tid))) | tag);
  PT(0, warp >> 2, 2);
  float* sc = sv + D_;
  if (tid < D_) {
    uint32_t vc, it = 0;
    do { vc = ld_rlx32(&g_mod[4 * D_ + tid]); if (++it > (1u << 22)) __trap(); } while ((vc & 0xFFFFu) != tag);
    sc[tid] = bf_round(1.0f + bf_hi(vc));
  }
  __syncthreads();
  mbar_wait(bar + 16, 0);
  PT(0, warp >> 2, 5);
  if (tid < 448) {
    const int nc = (tid % 112) >> 3, rl = (tid / 112) * 8 + (tid & 7);
    const uint32_t src = sm + K1_AUXX + rl * 224 + nc * 16;
    uint8_t* dst = g_wimg + ax * 7 * 14336 + nc * 1024 + rl * 16;
    uint4 v[14]; uint32_t s2[14];
#pragma unroll
    for (int i = 0; i < 14; i++) { v[i] = lds128(src + i * 32 * 224); s2[i] = __float_as_uint(sc[rl + 32 * i]); }
#pragma unroll
    for (int i = 0; i < 14; i++) {
      const uint32_t m = prmt(s2[i], 0, 0x3232);
      *(uint4*)(dst + (i >> 1) * 14336 + (i & 1) * 512) = make_uint4(hmul2(v[i].x, m), hmul2(v[i].y, m), hmul2(v[i].z, m), hmul2(v[i].w, m));
    }
  }
  __syncthreads();
  if (tid == 480) { asm volatile("fence.acq_rel.gpu;" ::: "memory"); pdl_launch(); }
  PT(0, warp >> 2, 6);
  mbar_wait(bar + 8, 0);
  aux_gemv<7, false>(sm + K1_AUXY, sv, sv, red, warp, lane);
  __syncthreads();
  if (tid < 56) st_rlx32(&g_mod[c2 + tid], __float_as_uint(bf_round(aux_sum16(red, tid))) | tag);
  PT(0, warp >> 2, 4);
  if (tid < D_) {
    uint32_t vs, it = 0;
    do { vs = ld_rlx32(&g_mod[3 * D_ + tid]); if (++it > (1u << 22)) __trap(); } while ((vs & 0xFFFFu) != tag);
    sv[tid] = bf_hi(vs);
  }
  __syncthreads();
  aux_gemv<14, true>(sm + K1_AUXX, sc, sv, red, warp, lane);
  __syncthreads();
  if (tid < 224) {
    const int nc = tid >> 4, kr = tid & 15;
    uint32_t o[4] = {0u, 0u, 0u, 0u};
    if (kr < 4) {
#pragma unroll
      for (int j = 0; j < 4; j++) {
        const float x = aux_sum16(red, (kr >> 1) * 112 + nc * 8 + 2 * j), y = aux_sum16(red, (kr >> 1) * 112 + nc * 8 + 2 * j + 1);
        o[j] = (kr & 1) ? pack_bf16(x - bf_round(x), y - bf_round(y)) : pack_bf16(x, y);
      }
    }
    *(uint4*)(g_waug + ax * 3584 + tid * 16) = make_uint4(o[0], o[1], o[2], o[3]);
  }
  PT(0, warp >> 2, 10);
}

__global__ void __launch_bounds__(512, 1) k1_conv(const K1Args a, const __grid_constant__ CUtensorMap tm_wmod1, const __grid_constant__ CUtensorMap tm_wmod2, const __grid_constant__ CUtensorMap tm_win) {
  extern __shared__ __align__(1024) uint8_t smem_raw[];
  const uint32_t sm = smem_u32(smem_raw);
  const int tid = threadIdx.x, warp = __shfl_sync(~0u, tid >> 5, 0), lane = tid & 31, cta = blockIdx.x;
  const int g = lane >> 2, t4 = lane & 3;
  const int d0 = cta * 4;
  const uint32_t s_modv = sm + K1_MISC, s_kv1024 = sm + K1_MISC + 96;
  const int wg = warp >> 2, w4 = warp & 3, t = tid & 127;
  PT(0, wg, 0);
  const uint32_t tagraw = ldg32_nc(&g_epoch);
  if (cta >= 112) { k1_aux(a, &tm_wmod1, &tm_wmod2, &tm_win, smem_raw, tid, warp, lane, cta, tagraw); return; }
  const int po = (d0 + wg) * NM_ + 2 * t;
  const uint32_t pAre = ldg32_nc(a.Are + po), pAim = ldg32_nc(a.Aim + po), pBre = ldg32_nc(a.Bre + po), pBim = ldg32_nc(a.Bim + po), pCre = ldg32_nc(a.Cre + po), pCim = ldg32_nc(a.Cim + po);
  const uint32_t ldtr = ldg16_nc(a.logdt + d0 + wg);
  uint4 ur0 = make_uint4(0, 0, 0, 0), ur1 = ur0;
  if (lane < 28) { const bf16* p = a.u + (cta * 16 + warp) * D_ + lane * 16; ur0 = ldg128_nc(p); ur1 = ldg128_nc(p + 8); }
  const uint32_t dskr = ldg16_nc(a.dskip + d0 + wg);
  uint32_t km[5];
#pragma unroll
  for (int i = 0; i < 5; i++) km[i] = ldg32_nc(&g_kmap.v[t + 128 * i]);
  if (tid == 32) pdl_launch();
  if (tid < 4 * 8 * 9) sts128(sm + K1_H + (tid / 72) * K1_HSZ + ((tid % 72) / 9) * K1_CS + (tid % 9) * 16, make_uint4(0, 0, 0, 0));
  const uint32_t tag = (tagraw + 1u) & 0xFFFFu;
  ln1_stage(ur0, ur1, sm + K1_S, warp, lane);
  if (tid == 64) l2_prefetch((const uint8_t*)a.w_mod + cta * 18816, 18816);
  ln1_rows(ur0, ur1, sm + K1_S, tid, warp, lane, cta, tag);
  PT(0, wg, 1);
  uint4 wo = make_uint4(0, 0, 0, 0);
  if (tid == 480) l2_prefetch((const uint8_t*)a.w_in + cta * 14336, 14336);
  if (tid < 448) wo = ldg128_nc(a.w_out + (cta * 8 + (tid & 7)) * D_ + (tid >> 3) * 8);

  const uint32_t R = sm + K1_R + wg * K1_RSZ;
  const uint32_t tlo = R + w4 * 7168, thi = tlo + 4096;
  float kacc[2][3][4];
#pragma unroll
  for (int i = 0; i < 2; i++)
#pragma unroll
    for (int j = 0; j < 3; j++)
#pragma unroll
      for (int k = 0; k < 4; k++) kacc[i][j][k] = 0.f;
  {
    const float dt = bf_round(expf(bf_lo(ldtr)));
    const uint32_t lb = ((lane >> 2) << 4) | ((lane & 3) << 2);
#pragma unroll 1
    for (int p = 0; p < 2; p++) {
      const float ar = dt * (p ? bf_hi(pAre) : bf_lo(pAre)), ai = dt * (p ? bf_hi(pAim) : bf_lo(pAim));
      const cplx db = {dt * (p ? bf_hi(pBre) : bf_lo(pBre)), dt * (p ? bf_hi(pBim) : bf_lo(pBim))};
      const cplx cc = {p ? bf_hi(pCre) : bf_lo(pCre), p ? bf_hi(pCim) : bf_lo(pCim)};
      cplx w = cmul(cc, db);
      w.i = -w.i;
      const cplx E1 = cexp_p(ar, -ai, 1.f), E8 = cexp_p(ar, ai, 8.f), E128 = cexp_p(ar, ai, 128.f);
#define ST_LO(j, v) sts32(tlo + (j) * 128 + (lb ^ (((j) & 7) << 4)), pack_bf16((v).r, (v).i))
#define ST_HI(j, v) sts32(thi + (j) * 128 + (lb ^ (((j) & 7) << 4)), pack_bf16((v).r, (v).i))
      if (p) __syncwarp();
      {
        cplx ya = {1.f, 0.f}, yb = E128, x = w;
        ST_LO(0, ya); ST_LO(16, yb); ST_HI(0, x);
        ya = E8; yb = cmul(yb, E8); x = cmul(x, E1);
        ST_LO(1, ya); ST_LO(17, yb); ST_HI(1, x);
        const cplx E2 = csq(E1), E4 = csq(E2);
        cplx E256 = csq(E128); E256.i = -E256.i;
        cplx b = cmul(w, E256);
#pragma unroll
        for (int j = 2; j < 16; j++) {
          ya = cmul(ya, E8); yb = cmul(yb, E8);
          ST_LO(j, ya); ST_LO(16 + j, yb);
          if (j < 8) { x = cmul(x, E1); ST_HI(j, x); }
          if (j == 2) { ST_HI(8, b); }
          if (j == 8) { x = cmul(b, E2); ST_HI(9, x); b = cmul(b, E256); ST_HI(12, b); }
          if (j == 9) { x = cmul(x, E2); ST_HI(10, x); const cplx y = cmul(b, E4); ST_HI(13, y); b = cmul(b, E256); ST_HI(14, b); }
          if (j == 10) { x = cmul(x, E2); ST_HI(11, x); const cplx y = cmul(b, E4); ST_HI(15, y); }
          if (j >= 11) { b = cmul(b, E256); ST_HI(5 + j, b); }
        }
      }
      __syncwarp();
#pragma unroll
      for (int k2 = 0; k2 < 2; k2++) {
        uint32_t bfr[3][4];
#pragma unroll
        for (int nt = 0; nt < 3; nt++) {
          const int row = nt * 8 + (lane & 7), ch = k2 * 4 + (lane >> 3);
          ldsm4(thi + row * 128 + ((ch ^ (row & 7)) << 4), bfr[nt][0], bfr[nt][1], bfr[nt][2], bfr[nt][3]);
        }
#pragma unroll
        for (int kk = 0; kk < 2; kk++)
#pragma unroll
          for (int mt = 0; mt < 2; mt++) {
            uint32_t a0, a1, a2, a3;
            const int row = mt * 16 + (lane & 15), ch = k2 * 4 + kk * 2 + (lane >> 4);
            ldsm4(tlo + row * 128 + ((ch ^ (row & 7)) << 4), a0, a1, a2, a3);
#pragma unroll
            for (int nt = 0; nt < 3; nt++) mma16816(kacc[mt][nt], a0, a1, a2, a3, bfr[nt][2 * kk], bfr[nt][2 * kk + 1]);
          }
      }
    }
    __syncwarp();
#pragma unroll
    for (int mt = 0; mt < 2; mt++)
#pragma unroll
      for (int nt = 0; nt < 3; nt++) {
        sts64f(tlo + ((mt * 16 + g) * 24 + nt * 8 + 2 * t4) * 4, kacc[mt][nt][0], kacc[mt][nt][1]);
        sts64f(tlo + ((mt * 16 + g + 8) * 24 + nt * 8 + 2 * t4) * 4, kacc[mt][nt][2], kacc[mt][nt][3]);
      }
  }
  PT(0, wg, 3);
  if (tid < 448) {
    const int f = cta * 8 + (tid & 7), dc = tid >> 3;
    *(uint4*)(g_woimg + ((dc / 14) * 8 + f / 112) * 25088 + (dc % 14) * 1792 + ((f % 112) >> 3) * 128 + (f & 7) * 16) = wo;
  }
  {
    uint32_t it = 0;
    while ((ld_acq64(&g_stat1[4 * tid]).x & 0xFFFFu) != tag) if (++it > (1u << 22)) __trap();
  }
  PT(0, wg, 2);
  uint4 st01 = ld_rlx2x64(&g_stat1[4 * tid]), st23 = ld_rlx2x64(&g_stat1[4 * tid + 2]);
  const uint4 uqa = ldg128_cg(&g_uT[cta * 1024 + 2 * tid]), uqb = ldg128_cg(&g_uT[cta * 1024 + 2 * tid + 1]);
  uint32_t modraw = 0;
  if (tid < 12) modraw = ld_rlx32(&g_mod[(tid >> 2) * D_ + d0 + (tid & 3)]);
  bar_sync(2 + wg, 128);
  const uint32_t KV = sm + K1_KV + wg * K1_KVSZ;
  {
    float2 pv[3][4];
#pragma unroll
    for (int i = 0; i < 3; i++)
#pragma unroll
      for (int w = 0; w < 4; w++) pv[i][w] = lds64f(R + w * 7168 + (t + 128 * i) * 8);
#pragma unroll
    for (int i = 0; i < 3; i++) {
      const float sx = (pv[i][0].x + pv[i][1].x) + (pv[i][2].x + pv[i][3].x), sy = (pv[i][0].y + pv[i][1].y) + (pv[i][2].y + pv[i][3].y);
      const int pr = t + 128 * i, j = pr / 12, ii = 2 * (pr % 12);
      const uint32_t pk = pack_bf16(sx, sy);
      sts16(KV + (ii * 40 + j) * 2, pk); sts16(KV + (ii * 40 + 40 + j) * 2, pk >> 16);
      if (i == 0 && t == 8) sts32f(s_kv1024 + wg * 4, sx);
    }
    if (t == 0) sts16(KV + KV_ZERO * 2, 0u);
  }
  if (tid < 12) {
    uint32_t it = 0;
    while ((modraw & 0xFFFFu) != tag) { modraw = ld_rlx32(&g_mod[(tid >> 2) * D_ + d0 + (tid & 3)]); if (++it > (1u << 22)) __trap(); }
    sts32(s_modv + tid * 4, modraw & 0xFFFF0000u);
  }
  PT(0, wg, 5);
  __syncthreads();
  {
    uint32_t e0[5], e1[5], e2[5];
#pragma unroll
    for (int i = 0; i < 5; i++) { e0[i] = lds16(KV + (km[i] & 1023u) * 2); e1[i] = lds16(KV + ((km[i] >> 10) & 1023u) * 2); e2[i] = lds16(KV + (km[i] >> 20) * 2); }
#pragma unroll
    for (int i = 0; i < 5; i++) { sts32(R + K1_Z0 + (t + 128 * i) * 4, e0[i] | (e1[i] << 16)); sts32(R + K1_Z1 + (t + 128 * i) * 4, e1[i] | (e2[i] << 16)); }
  }
  PT(0, wg, 4);
  {
    for (uint32_t it = 0; ((st01.x ^ tag) | (st01.z ^ tag) | (st23.x ^ tag) | (st23.z ^ tag)) & 0xFFFFu;) {
      st01 = ld_rlx2x64(&g_stat1[4 * tid]); st23 = ld_rlx2x64(&g_stat1[4 * tid + 2]);
      if (++it > (1u << 22)) __trap();
    }
    const float4 sa = lds128f(s_modv), ca = lds128f(s_modv + 16);
    const uint2 uq[4] = {make_uint2(uqa.x, uqa.y), make_uint2(uqa.z, uqa.w), make_uint2(uqb.x, uqb.y), make_uint2(uqb.z, uqb.w)};
    const uint32_t sa01 = pack_bf16(sa.x, sa.y), sa23 = pack_bf16(sa.z, sa.w);
    const uint32_t ca01 = pack_bf16(1.f + ca.x, 1.f + ca.y), ca23 = pack_bf16(1.f + ca.z, 1.f + ca.w);
    const uint32_t mm[4] = {st01.x, st01.z, st23.x, st23.z};
    const float rr[4] = {__uint_as_float(st01.y), __uint_as_float(st01.w), __uint_as_float(st23.y), __uint_as_float(st23.w)};
    uint32_t h01[4], h23[4];
#pragma unroll
    for (int r = 0; r < 4; r++) {
      const uint32_t m2 = prmt(mm[r], mm[r], 0x3232);
      uint32_t dd = hsub2(uq[r].x, m2);
      h01[r] = hadd2(hmul2(pack_bf16(bf_lo(dd) * rr[r], bf_hi(dd) * rr[r]), ca01), sa01);
      dd = hsub2(uq[r].y, m2);
      h23[r] = hadd2(hmul2(pack_bf16(bf_lo(dd) * rr[r], bf_hi(dd) * rr[r]), ca23), sa23);
    }
    const uint32_t ho = h_chunk(sm + K1_H, tid >> 1) + ((tid & 1) ? 0 : 8), uo = sm + K1_U + tid * 8;
    sts64(ho, prmt(h01[3], h01[2], 0x5410), prmt(h01[1], h01[0], 0x5410));
    sts64(ho + K1_HSZ, prmt(h01[3], h01[2], 0x7632), prmt(h01[1], h01[0], 0x7632));
    sts64(ho + 2 * K1_HSZ, prmt(h23[3], h23[2], 0x5410), prmt(h23[1], h23[0], 0x5410));
    sts64(ho + 3 * K1_HSZ, prmt(h23[3], h23[2], 0x7632), prmt(h23[1], h23[0], 0x7632));
    sts64(uo, prmt(uq[0].x, uq[1].x, 0x5410), prmt(uq[2].x, uq[3].x, 0x5410));
    sts64(uo + 4096, prmt(uq[0].x, uq[1].x, 0x7632), prmt(uq[2].x, uq[3].x, 0x7632));
    sts64(uo + 8192, prmt(uq[0].y, uq[1].y, 0x5410), prmt(uq[2].y, uq[3].y, 0x5410));
    sts64(uo + 12288, prmt(uq[0].y, uq[1].y, 0x7632), prmt(uq[2].y, uq[3].y, 0x7632));
  }
  fence_async_smem();
  __syncthreads();
  PT(0, wg, 6);
  if (tid >= 480 && tid < 485) l2_prefetch((const uint8_t*)a.w_sp + (size_t)cta * 74880 + (tid - 480) * 14976, cta == 111 && tid == 484 ? 14976 + 2048 : 14976);
  const uint32_t H = sm + K1_H + wg * K1_HSZ, S = sm + K1_S + wg * K1_SSZ;
  float D0[16], D2[12], D3a[16], D3b[8];
  const uint32_t za = R + ((g & 1) ? K1_Z1 : K1_Z0) + (8 * w4 + (g >> 1) + t4) * 4;
  const uint64_t dH = mkdesc(H + 9 * 16, desc_hi(K1_CS, 128, 0)), dS = mkdesc(S, desc_hi(144, 1152, 0)), dS2 = mkdesc(S + K1_EO, desc_hi(144, 2304, 0));
  uint32_t prev = lds32(za);
  uint32_t sv[8];
#define CONV_LOAD(G)  _Pragma("unroll") for (int i = 0; i < 8; i++) if (4 * (G) + i / 2 < 61) sv[i] = lds32(za + (8 * (G) + i + 1) * 16);
#define CONV_ISSUE(G)                                                                                                        \
  {                                                                                                                          \
    uint32_t cur[8];                                                                                                         \
    _Pragma("unroll") for (int i = 0; i < 8; i++) cur[i] = sv[i];                                                            \
    wg_fence();                                                                                                              \
    _Pragma("unroll") for (int i = 0; i < 4; i++) {                                                                          \
      const int s = 4 * (G) + i;                                                                                             \
      if (s < 61) {                                                                                                          \
        const uint32_t a0 = prev, a1 = cur[2 * i], a3 = cur[2 * i + 1];                                                      \
        if (s < 37) wgmma_rs_n32(D0, a0, a1, a1, a3, dH + (uint64_t)((2 * (s & 3)) * (K1_CS / 16)) - (uint64_t)(s >> 2), s > 0); \
        else if (s < 41) wgmma_rs_n24(D2, a0, a1, a1, a3, dS + (K1_S5 / 16 + (s - 37) * 18), s > 37);                        \
        else if (s < 45) wgmma_rs_n16(D2, a0, a1, a1, a3, dS + (K1_S5 / 16 + (s - 37) * 18), 1);                             \
        else if (s < 49) wgmma_rs_n24(D2, a0, a1, a1, a3, dS + (K1_S3 / 16 + (s - 45) * 18), 1);                             \
        else if (s < 53) wgmma_rs_n16(D2, a0, a1, a1, a3, dS + (K1_S3 / 16 + (s - 45) * 18), 1);                             \
        else if (s < 57) wgmma_rs_n32(D3a, a0, a1, a1, a3, dS + (K1_EO / 16 + (s - 53) * 18), s > 53);                       \
        else wgmma_rs_n16(D3b, a0, a1, a1, a3, dS2 + (s - 53) * 18, s > 57);                                                 \
        prev = a3;                                                                                                           \
      }                                                                                                                      \
    }                                                                                                                        \
    wg_commit();                                                                                                             \
  }
  {
    const int cb = 8 * (w4 >> 1) + (w4 & 1);
    const int qa = 190 - (64 + 8 * (cb + 2 * t4) + g), qb = 190 - (8 * ((w4 & 1) + 2 * t4) + g);
    uint4 ra[3], rb[3];
#pragma unroll
    for (int i = 0; i < 3; i++) ra[i] = lds128(h_chunk(H, qa - 1 + i));
    if (w4 < 2) {
#pragma unroll
      for (int i = 0; i < 3; i++) rb[i] = lds128(h_chunk(H, qb - 1 + i));
    }
    const int cI = lane & 7, mj = lane >> 3;
    const uint32_t ro = (2 * (cI >> 1)) * 144 + (2 * mj + (cI & 1)) * 16;
    float hh[24], c[22];
    unpack_rev(ra[0], hh); unpack_rev(ra[1], hh + 8); unpack_rev(ra[2], hh + 16);
    c[4] = 0.f;
#pragma unroll
    for (int i = 4; i < 21; i++) c[i + 1] = c[i] + hh[i];
    uint32_t r5[4], r3[4], re[4], rz[4];
#pragma unroll
    for (int j = 0; j < 4; j++) {
      r5[j] = pack_bf16(c[11 + 2 * j] - c[6 + 2 * j], c[12 + 2 * j] - c[7 + 2 * j]);
      r3[j] = pack_bf16(c[14 + 2 * j] - c[11 + 2 * j], c[15 + 2 * j] - c[12 + 2 * j]);
      const uint32_t s9 = pack_bf16(c[13 + 2 * j] - c[4 + 2 * j], c[14 + 2 * j] - c[5 + 2 * j]);
      const uint32_t s7 = pack_bf16(c[12 + 2 * j] - c[5 + 2 * j], c[13 + 2 * j] - c[6 + 2 * j]);
      re[j] = (g & 1) ? s7 : s9; rz[j] = (g & 1) ? s9 : s7;
    }
    stsm4t(S + K1_S5 + (8 + cb) * 144 + ro, r5[0], r5[1], r5[2], r5[3]);
    stsm4t(S + K1_S3 + (8 + cb) * 144 + ro, r3[0], r3[1], r3[2], r3[3]);
    stsm4t(S + K1_EO + cb * 144 + ro, re[0], re[1], re[2], re[3]);
    stsm4t(S + K1_EO + 2304 + cb * 144 + ro, rz[0], rz[1], rz[2], rz[3]);
    if (w4 < 2) {
      unpack_rev(rb[0], hh); unpack_rev(rb[1], hh + 8); unpack_rev(rb[2], hh + 16);
      c[6] = 0.f;
#pragma unroll
      for (int i = 6; i < 21; i++) c[i + 1] = c[i] + hh[i];
#pragma unroll
      for (int j = 0; j < 4; j++) {
        r5[j] = pack_bf16(c[11 + 2 * j] - c[6 + 2 * j], c[12 + 2 * j] - c[7 + 2 * j]);
        r3[j] = pack_bf16(c[14 + 2 * j] - c[11 + 2 * j], c[15 + 2 * j] - c[12 + 2 * j]);
      }
      stsm4t(S + K1_S5 + (w4 & 1) * 144 + ro, r5[0], r5[1], r5[2], r5[3]);
      stsm4t(S + K1_S3 + (w4 & 1) * 144 + ro, r3[0], r3[1], r3[2], r3[3]);
    }
  }
  fence_async_smem();
  CONV_LOAD(0)
  bar_sync(2 + wg, 128);
  PT(0, wg, 7);
#define CONV_STEP(G) CONV_ISSUE(G) CONV_LOAD((G) + 1) wg_wait<1>();
  CONV_STEP(0) CONV_STEP(1) CONV_STEP(2) CONV_STEP(3) CONV_STEP(4) CONV_STEP(5) CONV_STEP(6) CONV_STEP(7)
  CONV_STEP(8) CONV_STEP(9) CONV_STEP(10) CONV_STEP(11) CONV_STEP(12) CONV_STEP(13) CONV_STEP(14) CONV_ISSUE(15)
  wg_wait<0>();
  fence_regs<16>(D0); fence_regs<12>(D2); fence_regs<16>(D3a); fence_regs<8>(D3b);
  PT(0, wg, 8);
  {
    const uint32_t Y0 = R + K1_Y0, Y2 = R + K1_Y2;
#pragma unroll
    for (int j = 0; j < 4; j++)
#pragma unroll
      for (int e = 0; e < 4; e++) {
        const int l = 64 * (8 * j + 2 * t4 + (e & 1)) + 16 * w4 + g + 8 * (e >> 1);
        sts32f(Y0 + ypad(l) * 4, D0[4 * j + e]);
      }
    const bool odd = g & 1;
#pragma unroll
    for (int e = 0; e < 4; e++) {
      D2[e] += (odd ? D3a[8 + e] : D3a[e]) + (odd ? D3b[4 + e] : D3b[e]);
      D2[4 + e] += odd ? D3a[12 + e] : D3a[4 + e];
    }
#pragma unroll
    for (int gm = 0; gm < 3; gm++)
#pragma unroll
      for (int hf = 0; hf < 2; hf++) {
        const int l2 = 8 * (16 * w4 + g + 8 * hf) + 2 * t4 + 512 * (2 - gm);
        sts64f(Y2 + ypad(l2) * 4, D2[4 * gm + 2 * hf], D2[4 * gm + 2 * hf + 1]);
      }
  }
  {
    const float kv = lds32f(s_kv1024 + wg * 4);
    const uint32_t dk2 = dskr * 0x10001u, ga2 = prmt(lds32(s_modv + (8 + wg) * 4), 0, 0x3232);
    const uint4 hm = lds128(h_chunk(H, t - 1)), h0 = lds128(h_chunk(H, t)), hp = lds128(h_chunk(H, t + 1)), h1 = lds128(h_chunk(H, t + 128));
    const uint4 u0 = lds128(sm + K1_U + wg * 4096 + t * 16), u1 = lds128(sm + K1_U + wg * 4096 + (t + 128) * 16);
    float f[8];
    {
      float hh[24], c[19];
      unpack_rev(hm, hh); unpack_rev(h0, hh + 8); unpack_rev(hp, hh + 16);
      c[4] = 0.f;
#pragma unroll
      for (int i = 4; i < 18; i++) c[i + 1] = c[i] + hh[i];
#pragma unroll
      for (int e = 0; e < 8; e++) f[e] = kv * (c[e + 11] - c[e + 4]);
    }
    float f6 = 0.f, f7 = 0.f;
    if (t == 127) { const uint32_t hw = lds32(h_chunk(H, 0) + 12); f6 = kv * bf_hi(hw); f7 = kv * (bf_hi(hw) + bf_lo(hw)); }
    bar_sync(2 + wg, 128);
    PT(0, wg, 9);
    float4 ya[2][2], yb[2][2];
#pragma unroll
    for (int hf = 0; hf < 2; hf++) {
      const int q = t + 128 * hf;
      ya[hf][0] = lds128f(R + K1_Y0 + ypad(8 * q) * 4); ya[hf][1] = lds128f(R + K1_Y0 + ypad(8 * q) * 4 + 16);
      if (q >= 64) { yb[hf][0] = lds128f(R + K1_Y2 + ypad(8 * q - 512) * 4); yb[hf][1] = lds128f(R + K1_Y2 + ypad(8 * q - 512) * 4 + 16); }
      else yb[hf][0] = yb[hf][1] = make_float4(0.f, 0.f, 0.f, 0.f);
    }
#pragma unroll
    for (int hf = 0; hf < 2; hf++) {
      const int q = t + 128 * hf;
      float y[8] = {ya[hf][0].x + yb[hf][0].x, ya[hf][0].y + yb[hf][0].y, ya[hf][0].z + yb[hf][0].z, ya[hf][0].w + yb[hf][0].w,
                    ya[hf][1].x + yb[hf][1].x, ya[hf][1].y + yb[hf][1].y, ya[hf][1].z + yb[hf][1].z, ya[hf][1].w + yb[hf][1].w};
      if (hf) {
#pragma unroll
        for (int e = 0; e < 8; e++) y[e] += f[e];
      } else { y[6] += f6; y[7] += f7; }
      const uint4 hv = hf ? h1 : h0, uv = hf ? u1 : u0;
      const uint32_t hn[4] = {prmt(hv.w, hv.w, 0x1032), prmt(hv.z, hv.z, 0x1032), prmt(hv.y, hv.y, 0x1032), prmt(hv.x, hv.x, 0x1032)};
      const uint32_t un[4] = {uv.x, uv.y, uv.z, uv.w};
      uint32_t x1[4];
#pragma unroll
      for (int j = 0; j < 4; j++) {
        x1[j] = hadd2(un[j], hmul2(ga2, hadd2(pack_bf16(y[2 * j], y[2 * j + 1]), hmul2(hn[j], dk2))));
      }
      *(uint4*)(g_x1T + (d0 + wg) * L_ + 8 * q) = make_uint4(x1[0], x1[1], x1[2], x1[3]);
    }
  }
  PT(0, wg, 10);
}

constexpr int KB_A = 0, KB_B = 114688, KB_X = KB_B + 7 * 14336, KB_AUG = KB_X + 7168, KB_RED = KB_AUG + 7168, KB_BAR = KB_RED + 1024, KB_SMEM = KB_BAR + 512;

__device__ __forceinline__ float gelu_half(float h) {
  const float u = h * fmaf(h * h, 0.2854192648f, 1.5957691216f);
  float t; asm("tanh.approx.f32 %0, %1;" : "=f"(t) : "f"(u));
  return fmaf(h, t, h);
}
template <int O, int X> __device__ __forceinline__ void tred(float* v, int lane) {
  const bool up = lane & X;
#pragma unroll
  for (int i = 0; i < O; i++) {
    const float snd = up ? v[i] : v[i + O], kp = up ? v[i + O] : v[i];
    v[i] = kp + __shfl_xor_sync(~0u, snd, X);
  }
}

template <int KAP>
__device__ __forceinline__ void kb_epilogue(const float* acc, const uint32_t* z1, uint32_t b0, uint32_t b1, uint32_t sm, int tid, int T, int j, uint32_t xfree, uint32_t xfull) {
  const int wg = tid >> 7, w4 = (tid >> 5) & 3, lane = tid & 31;
  const uint32_t xb = sm + KB_A + 2 * 16384 + tid * 16;
  const float* snd = acc + 56 * (KAP ^ 1);
  const float* kp = acc + 56 * KAP;
  mbar_wait(xfree, 0);
  {
    const uint32_t dst = mapa(xb, KAP ^ 1), rb = mapa(xfull, KAP ^ 1);
#pragma unroll
    for (int q = 0; q < 7; q++)
      asm volatile("st.async.shared::cluster.mbarrier::complete_tx::bytes.v4.b32 [%0], {%1,%2,%3,%4}, [%5];" ::"r"(dst + q * 4096), "r"(pack_bf16(snd[8 * q], snd[8 * q + 1])),
                   "r"(pack_bf16(snd[8 * q + 2], snd[8 * q + 3])), "r"(pack_bf16(snd[8 * q + 4], snd[8 * q + 5])), "r"(pack_bf16(snd[8 * q + 6], snd[8 * q + 7])), "r"(rb) : "memory");
  }
  PT(2, wg, 4);
  mbar_wait(xfull, 0);
  PT(2, wg, 5);
  uint8_t* dst = g_pimg + ((2 * T + wg) * 8 + 2 * j + KAP) * 14336 + (2 * w4) * 128 + lane * 4;
#pragma unroll
  for (int q = 0; q < 7; q++) {
    const uint4 v = lds128(xb + q * 4096);
    const uint32_t w[4] = {v.x, v.y, v.z, v.w};
#pragma unroll
    for (int i = 0; i < 4; i++)
      *(uint32_t*)(dst + (2 * q + (i >> 1)) * 1024 + (i & 1) * 128) =
          hmul2(z1[4 * q + i], hadd2(pack_bf16(kp[8 * q + 2 * i] + bf_lo(w[i]), kp[8 * q + 2 * i + 1] + bf_hi(w[i])), (i & 1) ? b1 : b0));
  }
  PT(2, wg, 6);
}

__global__ void __cluster_dims__(2, 1, 1) __launch_bounds__(384, 1)
kb_gemm12(const __grid_constant__ CUtensorMap tm_xs, const __grid_constant__ CUtensorMap tm_wsp, const bf16* __restrict__ b_sp) {
  extern __shared__ __align__(1024) uint8_t smem_raw[];
  const uint32_t sm = smem_u32(smem_raw);
  const int tid = threadIdx.x, warp = __shfl_sync(~0u, tid >> 5, 0), lane = tid & 31;
  const int T = blockIdx.x >> 3, ph = blockIdx.x & 7, j = ph >> 1, kap = ph & 1;
  const int wg = warp >> 2, w4 = warp & 3, g = lane >> 2, t4 = lane & 3;
  const uint32_t fullA = sm + KB_BAR, fullB = fullA + 56, emptyB = fullB + 112, barX = emptyB + 56, barG = barX + 8, bar1 = barG + 8;
  const uint32_t fullA2 = bar1 + 8, emptyA2 = fullA2 + 56, fullB2 = emptyA2 + 56, emptyB2 = fullB2 + 32, xfree = emptyB2 + 32, xfull = xfree + 8, relA = xfull + 8;
  const uint32_t sb = sm + KB_B;
  PT(1, wg, 0);
  const uint32_t tagraw = ldg32_nc(&g_epoch);
  if (tid == 256) {
    tmap_prefetch(&tm_xs); tmap_prefetch(&tm_wsp);
    for (int i = 0; i < 7; i++) { mbar_init(fullA + 8 * i, 1); mbar_init(emptyB + 8 * i, 2); mbar_init(fullA2 + 8 * i, 1); mbar_init(emptyA2 + 8 * i, 2); }
    for (int i = 0; i < 14; i++) mbar_init(fullB + 8 * i, 1);
    for (int i = 0; i < 4; i++) { mbar_init(fullB2 + 8 * i, 1); mbar_init(emptyB2 + 8 * i, 2); }
    mbar_init(barX, 1); mbar_init(barG, 1); mbar_init(bar1, 2); mbar_init(xfree, 2); mbar_init(xfull, 1); mbar_init(relA, 2);
    asm volatile("fence.mbarrier_init.release.cluster;" ::: "memory");
    mbar_expect_tx(xfull, 28672);
    for (int kb = 0; kb < 7; kb++) mbar_expect_tx(fullA + 8 * kb, 16384);
    for (int kb = 0; kb < 4; kb++) {
      mbar_expect_tx(fullB + 8 * kb, 14336);
      bulk_load(sb + kb * 14336, g_wimg + ((8 + ph) * 7 + kb) * 14336, 14336, fullB + 8 * kb);
    }
  }
  __syncthreads();
  asm volatile("barrier.cluster.arrive.relaxed.aligned;" ::: "memory");
  const uint32_t tag16 = (tagraw + 1u) & 0xFFFFu, tag = tag16 & 0xFFu;
  if (wg == 2) {
    asm volatile("barrier.cluster.wait.aligned;" ::: "memory");
    if (warp == 8) {
      if (lane == 0) {
        pdl_wait();
        PT(1, 2, 1);
        for (int kb = 0; kb < 7; kb++) {
          tma_load_2d_mc(sm + KB_A + kb * 16384 + kap * 8192, &tm_xs, T * 128 + kap * 64, kb * 64, fullA + 8 * kb, 3);
          if (kb >= 2 && kb < 5) {
            mbar_expect_tx(fullB + 8 * (kb + 2), 14336);
            bulk_load(sb + (kb + 2) * 14336, g_wimg + ((8 + ph) * 7 + kb + 2) * 14336, 14336, fullB + 8 * (kb + 2));
          }
        }
        mbar_expect_tx(barG, 7168);
        bulk_load(sm + KB_AUG, g_waug + (8 + ph) * 3584, 3584, barG);
        bulk_load(sm + KB_AUG + 3584, g_waug + ph * 3584, 3584, barG);
        pdl_launch();
        for (int kb = 0; kb < 7; kb++) {
          mbar_wait(emptyB + 8 * kb, 0);
          mbar_expect_tx(fullB + 8 * (7 + kb), 14336);
          bulk_load(sb + kb * 14336, g_wimg + (ph * 7 + kb) * 14336, 14336, fullB + 8 * (7 + kb));
        }
        mbar_wait(relA, 0);
        for (int kb = 0; kb < 3; kb++) {
          mbar_expect_tx(fullA2 + 8 * kb, 16384);
          tma_load_2d(sm + KB_A + kb * 16384, &tm_wsp, kap * 1024 + kb * 64, T * 128, fullA2 + 8 * kb);
        }
        mbar_wait(bar1, 0);
        PT(2, 2, 1);
        for (int kb = 3; kb < 5; kb++) {
          mbar_expect_tx(fullA2 + 8 * kb, 16384);
          tma_load_2d(sm + KB_A + kb * 16384, &tm_wsp, kap * 1024 + kb * 64, T * 128, fullA2 + 8 * kb);
        }
        const uint8_t* zsrc = g_z2img + ((size_t)(kap * 16) * 4 + j) * 28672;
        const uint32_t target = (tagraw + 1u) * 64u;
        int sa = 0;
        for (int kb = 0; kb < 16; kb++) {
          const int s = kb & 3;
          if (!(kb & 1)) {
            const unsigned int* cnt = &g_zcnt[(kap * 8 + (kb >> 1)) * 32];
            for (uint32_t it = 0;; it++) {
              unsigned int v; asm volatile("ld.acquire.gpu.global.u32 %0, [%1];" : "=r"(v) : "l"(cnt) : "memory");
              if ((int)(v - target) >= 0) break;
              if (it > (1u << 22)) __trap();
            }
            asm volatile("fence.proxy.async.global;" ::: "memory");
            if (kb == 0) PT(2, 2, 2);
          }
          if (kb >= 4) mbar_wait(emptyB2 + 8 * s, ((kb >> 2) & 1) ^ 1);
          mbar_expect_tx(fullB2 + 8 * s, 28672);
          bulk_load(sb + s * 28672, zsrc + (size_t)kb * 4 * 28672, 28672, fullB2 + 8 * s);
          if (kb < 2) {
            mbar_expect_tx(fullA2 + 8 * (5 + kb), 16384);
            tma_load_2d(sm + KB_A + (5 + kb) * 16384, &tm_wsp, kap * 1024 + (5 + kb) * 64, T * 128, fullA2 + 8 * (5 + kb));
          }
          if (kb >= 4 && kb < 13) {
            const int ka = kb + 3;
            mbar_wait(emptyA2 + 8 * sa, ka >= 14);
            mbar_expect_tx(fullA2 + 8 * sa, 16384);
            tma_load_2d(sm + KB_A + sa * 16384, &tm_wsp, kap * 1024 + ka * 64, T * 128, fullA2 + 8 * sa);
            if (++sa == 7) sa = 0;
          }
        }
      }
    } else {
      const int st = tid - 288;
      float v[16];
#pragma unroll
      for (int i = 0; i < 16; i++) v[i] = 0.f;
      const uint32_t c0 = (ph & 3) * 2 + (lane & 1);
#pragma unroll
      for (int h = 0; h < 2; h++) {
        uint4 xv[5];
#pragma unroll
        for (int i = 0; i < 4; i++) mbar_wait(fullA + 8 * (3 * h + i), 0);
        if (h) PT(1, 3, 4);
#pragma unroll
        for (int i = 0; i < 5; i++) {
          const int d = (st >> 1) + 48 * (5 * h + i);
          xv[i] = make_uint4(0u, 0u, 0u, 0u);
          if (d < D_) xv[i] = lds128(sm + KB_A + (d >> 6) * 16384 + (ph >> 2) * 8192 + (d & 63) * 128 + ((c0 ^ (d & 7)) << 4));
        }
#pragma unroll
        for (int i = 0; i < 5; i++) {
          const uint32_t q[4] = {xv[i].x, xv[i].y, xv[i].z, xv[i].w};
#pragma unroll
          for (int c = 0; c < 4; c++) {
            const float a = bf_lo(q[c]), b = bf_hi(q[c]);
            v[4 * c] += a; v[4 * c + 1] = fmaf(a, a, v[4 * c + 1]); v[4 * c + 2] += b; v[4 * c + 3] = fmaf(b, b, v[4 * c + 3]);
          }
        }
      }
      PT(1, 3, 3);
      tred<8, 16>(v, lane); tred<4, 8>(v, lane); tred<2, 4>(v, lane); tred<1, 2>(v, lane);
      sts32f(sm + KB_RED + (st >> 5) * 128 + ((lane & 1) * 16 + (lane >> 1)) * 4, v[0]);
      bar_sync(3, 96);
      if (st < 16) {
        float s = 0.f, q = 0.f;
#pragma unroll
        for (int w = 0; w < 3; w++) { const float2 p = lds64f(sm + KB_RED + w * 128 + st * 8); s += p.x; q += p.y; }
        const float mean = s * (1.0f / D_);
        const float var = fmaxf(q * (1.0f / D_) - mean * mean, 0.f);
        st_rlx64x(&g_stat2[T * 128 + ph * 16 + st], __float_as_uint(bf_round(mean)) | tag16, __float_as_uint(ln_den(var)));
      }
      PT(1, 3, 2);
    }
    return;
  }

  const int r0 = wg * 64 + w4 * 16 + g;
  const uint32_t b0 = ldg16_nc(b_sp + T * 128 + r0) * 0x10001u, b1 = ldg16_nc(b_sp + T * 128 + r0 + 8) * 0x10001u;
  const uint32_t peer_free = mapa(xfree, kap ^ 1);
  uint32_t z1[28];
  {
    const uint64_t da0 = mkdesc(sm + KB_A + wg * 8192, desc_hi(8192, 1024, 1)), db0 = mkdesc(sb, desc_hi(128, 1024, 0));
    const uint64_t daug = mkdesc(sm + KB_AUG, desc_hi(128, 256, 0));
    float a2[56], a1[56];
#define KB_MMA(i, kb, ACC)                                                                                                \
      mbar_wait(fullB + 8 * (i), 0);                                                                                      \
      wg_fence();                                                                                                         \
      _Pragma("unroll") for (int k = 0; k < 4; k++)                                                                       \
        wgmma_ss_n112<1, 1>(ACC, da0 + (kb) * 1024 + k * 128, db0 + (kb) * 896 + k * 16, ((kb) | k) != 0);                \
      wg_commit();
#pragma unroll 1
    for (int kb = 0; kb < 7; kb++) {
      mbar_wait(fullA + 8 * kb, 0);
      if (kb == 0) PT(1, wg, 1);
      KB_MMA(kb, kb, a2)
      if (kb >= 1) { wg_wait<1>(); if ((tid & 127) == 0) mbar_arrive(emptyB + 8 * (kb - 1)); }
    }
    PT(1, wg, 10);
    uint64_t v0, v1;
    for (uint32_t it = 0;; it++) {
      asm volatile("ld.relaxed.gpu.global.b64 %0, [%1];" : "=l"(v0) : "l"(&g_stat2[T * 128 + r0]) : "memory");
      asm volatile("ld.relaxed.gpu.global.b64 %0, [%1];" : "=l"(v1) : "l"(&g_stat2[T * 128 + r0 + 8]) : "memory");
      if (((((uint32_t)v0 ^ tag16) | ((uint32_t)v1 ^ tag16)) & 0xFFFFu) == 0) break;
      if (it > (1u << 22)) __trap();
    }
    __syncwarp();
    const uint32_t d0 = (uint32_t)(v0 >> 32), d1 = (uint32_t)(v1 >> 32);
    const uint32_t g0 = t4 == 0 ? prmt((uint32_t)v0, 0, 0x3232) ^ 0x80008000u : t4 == 1 ? prmt(d0, 0, 0x3232) : 0u;
    const uint32_t g1 = t4 == 0 ? prmt((uint32_t)v1, 0, 0x3232) ^ 0x80008000u : t4 == 1 ? prmt(d1, 0, 0x3232) : 0u;
    mbar_wait(barG, 0);
    wg_fence();
    wgmma_rs_n112_tb(a2, g0, g1, 0u, 0u, daug, 1);
    wg_commit();
    PT(1, wg, 3);
    KB_MMA(7, 0, a1)
    wg_wait<1>();
    fence_regs<56>(a2);
    if ((tid & 127) == 0) mbar_arrive(emptyB + 8 * 6);
    KB_MMA(8, 1, a1) KB_MMA(9, 2, a1)
    PT(1, wg, 2);
    const float rx = 0.5f / __uint_as_float(d0), ry = 0.5f / __uint_as_float(d1);
    {
      float s0 = 0.f, q0 = 0.f, s1 = 0.f, q1 = 0.f;
#pragma unroll
      for (int i = 0; i < 14; i++) {
        const float a = gelu_half(a2[4 * i] * rx), b = gelu_half(a2[4 * i + 1] * rx), c = gelu_half(a2[4 * i + 2] * ry), d = gelu_half(a2[4 * i + 3] * ry);
        a2[4 * i] = a; a2[4 * i + 1] = b; a2[4 * i + 2] = c; a2[4 * i + 3] = d;
        s0 += a + b; q0 = fmaf(a, a, fmaf(b, b, q0));
        s1 += c + d; q1 = fmaf(c, c, fmaf(d, d, q1));
      }
#pragma unroll
      for (int o = 1; o < 4; o <<= 1) { s0 += __shfl_xor_sync(~0u, s0, o); q0 += __shfl_xor_sync(~0u, q0, o); s1 += __shfl_xor_sync(~0u, s1, o); q1 += __shfl_xor_sync(~0u, q1, o); }
      q0 = fmaxf(fmaf(-s0, s0 * (1.0f / 112.f), q0), 0.f); q1 = fmaxf(fmaf(-s1, s1 * (1.0f / 112.f), q1), 0.f);
      if (t4 < 2) st_rlx64x(&g_zstat[(T * 8 + ph) * 128 + r0 + 8 * t4], __float_as_uint(t4 ? s1 : s0), (__float_as_uint(t4 ? q1 : q0) & ~0xFFu) | tag);
    }
    PT(1, wg, 4);
    KB_MMA(10, 3, a1) KB_MMA(11, 4, a1)
    wg_wait<2>();
    if ((tid & 127) == 0) mbar_arrive(relA);
    {
      uint64_t p[4];
      for (uint32_t it = 0;; it++) {
#pragma unroll
        for (int i = 0; i < 4; i++) asm volatile("ld.relaxed.gpu.global.b64 %0, [%1];" : "=l"(p[i]) : "l"(&g_zstat[(T * 8 + t4 + 4 * (i >> 1)) * 128 + r0 + 8 * (i & 1)]) : "memory");
        if (!((((uint32_t)(p[0] >> 32) ^ tag) | ((uint32_t)(p[1] >> 32) ^ tag) | ((uint32_t)(p[2] >> 32) ^ tag) | ((uint32_t)(p[3] >> 32) ^ tag)) & 0xFFu)) break;
        if (it > (1u << 22)) __trap();
      }
      __syncwarp();
      PT(1, wg, 7);
      const float sa0 = __uint_as_float((uint32_t)p[0]), sa1 = __uint_as_float((uint32_t)p[1]), sb0 = __uint_as_float((uint32_t)p[2]), sb1 = __uint_as_float((uint32_t)p[3]);
      float s0 = sa0 + sb0, s1 = sa1 + sb1;
#pragma unroll
      for (int o = 1; o < 4; o <<= 1) { s0 += __shfl_xor_sync(~0u, s0, o); s1 += __shfl_xor_sync(~0u, s1, o); }
      const float m0 = s0 * (1.0f / FH_), m1 = s1 * (1.0f / FH_);
      float da = fmaf(sa0, 1.0f / 112.f, -m0), db = fmaf(sb0, 1.0f / 112.f, -m0);
      float q0 = __uint_as_float((uint32_t)(p[0] >> 32)) + __uint_as_float((uint32_t)(p[2] >> 32)) + 112.f * fmaf(da, da, db * db);
      da = fmaf(sa1, 1.0f / 112.f, -m1); db = fmaf(sb1, 1.0f / 112.f, -m1);
      float q1 = __uint_as_float((uint32_t)(p[1] >> 32)) + __uint_as_float((uint32_t)(p[3] >> 32)) + 112.f * fmaf(da, da, db * db);
#pragma unroll
      for (int o = 1; o < 4; o <<= 1) { q0 += __shfl_xor_sync(~0u, q0, o); q1 += __shfl_xor_sync(~0u, q1, o); }
      const float i0 = ln_rden(q0 * (1.0f / FH_)), i1 = ln_rden(q1 * (1.0f / FH_));
      const float o0 = -bf_round(m0) * i0, o1 = -bf_round(m1) * i1;
      PT(1, wg, 11);
      uint8_t* dst = g_z2img + ((2 * T + wg) * 4 + j) * 28672 + kap * 14336 + (2 * w4) * 128 + lane * 4;
#pragma unroll
      for (int i = 0; i < 14; i++) {
        *(uint32_t*)(dst + i * 1024) = pack_bf16(fmaf(a2[4 * i], i0, o0), fmaf(a2[4 * i + 1], i0, o0));
        *(uint32_t*)(dst + i * 1024 + 128) = pack_bf16(fmaf(a2[4 * i + 2], i1, o1), fmaf(a2[4 * i + 3], i1, o1));
      }
    }
    PT(1, wg, 12);
    KB_MMA(12, 5, a1)
    mbar_wait(fullB + 8 * 13, 0);
    wg_fence();
#pragma unroll
    for (int k = 0; k < 4; k++) wgmma_ss_n112<1, 1>(a1, da0 + 6 * 1024 + k * 128, db0 + 6 * 896 + k * 16, 1);
    wgmma_rs_n112_tb(a1, g0, g1, 0u, 0u, daug + 224, 1);
    wg_commit();
    PT(1, wg, 13);
    __syncwarp();
    if (lane == 0) asm volatile("red.release.gpu.global.add.u32 [%0], 1;" ::"l"(&g_zcnt[T * 32]) : "memory");
    __syncwarp();
    PT(1, wg, 8);
    wg_wait<0>();
    fence_regs<56>(a1);
    if ((tid & 127) == 0) mbar_arrive(bar1);
    PT(1, wg, 5);
#pragma unroll
    for (int i = 0; i < 28; i++) { const float rr = (i & 1) ? ry : rx; z1[i] = pack_bf16(gelu_half(a1[2 * i] * rr), gelu_half(a1[2 * i + 1] * rr)); }
    PT(1, wg, 6);
  }
  float acc[112];
  const uint64_t dA = mkdesc(sm + KB_A + wg * 8192, desc_hi(16, 1024, 1)), dB = mkdesc(sb, desc_hi(128, 1024, 0));
  asm volatile("barrier.cluster.wait.aligned;" ::: "memory");
  int sa = 0, pa = 0;
#pragma unroll 1
  for (int kb = 0; kb < 16; kb++) {
    mbar_wait(fullA2 + 8 * sa, pa);
    mbar_wait(fullB2 + 8 * (kb & 3), (kb >> 2) & 1);
    if (kb == 0) PT(2, wg, 1);
    if (kb == 8) PT(2, wg, 2);
    wg_fence();
#pragma unroll
    for (int k = 0; k < 4; k++) wgmma_ss_n224<0, 1>(acc, dA + sa * 1024 + k * 2, dB + (kb & 3) * 1792 + k * 16, (kb | k) != 0);
    wg_commit();
    if (kb > 0) {
      wg_wait<1>();
      if ((tid & 127) == 0) {
        mbar_arrive(emptyB2 + 8 * ((kb - 1) & 3));
        if (kb <= 9) mbar_arrive(emptyA2 + 8 * (sa == 0 ? 6 : sa - 1));
        if (kb == 11) mbar_arrive_remote(peer_free);
      }
    }
    if (++sa == 7) { sa = 0; pa ^= 1; }
  }
  wg_wait<0>();
  fence_regs<112>(acc);
  PT(2, wg, 3);
  if (kap == 0) kb_epilogue<0>(acc, z1, b0, b1, sm, tid, T, j, xfree, xfull);
  else kb_epilogue<1>(acc, z1, b0, b1, sm, tid, T, j, xfree, xfull);
}

constexpr int K4_X = 0, K4_A = 14336, K4_B = K4_A + 4 * 14336, K4_GB = K4_B + 6 * 25088, K4_BAR = K4_GB + 256, K4_SMEM = K4_BAR + 256;

__global__ void __launch_bounds__(160, 1) k4_gemm3(const __grid_constant__ CUtensorMap tm_x1, const __grid_constant__ CUtensorMap tm_out) {
  extern __shared__ __align__(1024) uint8_t smem_raw[];
  const uint32_t sm = smem_u32(smem_raw);
  const int tid = threadIdx.x, warp = __shfl_sync(~0u, tid >> 5, 0), lane = tid & 31;
  const int Rt = blockIdx.x >> 2, c = blockIdx.x & 3;
  const uint32_t fullA = sm + K4_BAR, fullB = fullA + 64, done = fullB + 64, fullX = done + 64;
  const uint8_t* wsrc = g_woimg + c * 8 * 25088;
  PT(3, warp >> 2, 0);
  if (tid == 128) {
    tmap_prefetch(&tm_x1); tmap_prefetch(&tm_out);
    for (int i = 0; i < 8; i++) { mbar_init(fullA + 8 * i, 1); mbar_init(fullB + 8 * i, 1); mbar_init(done + 8 * i, 1); }
    mbar_init(fullX, 1);
    asm volatile("fence.mbarrier_init.release.cluster;" ::: "memory");
    for (int p = 0; p < 6; p++) { mbar_expect_tx(fullB + 8 * p, 25088); bulk_load(sm + K4_B + p * 25088, wsrc + p * 25088, 25088, fullB + 8 * p); }
    mbar_expect_tx(fullX, 14336);
    tma_load_2d(sm + K4_X, &tm_x1, Rt * 64, c * 112, fullX);
  }
  if (tid < 56) sts32(sm + K4_GB + tid * 4, prmt(__ldcg(&g_mod[5 * D_ + c * 112 + 2 * tid]), __ldcg(&g_mod[5 * D_ + c * 112 + 2 * tid + 1]), 0x7632));
  __syncthreads();
  if (warp == 4) {
    if (lane == 0) {
      pdl_wait();
      PT(3, 1, 1);
      if (blockIdx.x == 0) g_epoch = g_epoch + 1u;
      const uint8_t* asrc = g_pimg + Rt * 8 * 14336;
      for (int p = 0; p < 8; p++) {
        if (p >= 4) mbar_wait(done + 8 * (p - 4), 0);
        mbar_expect_tx(fullA + 8 * p, 14336);
        bulk_load(sm + K4_A + (p & 3) * 14336, asrc + p * 14336, 14336, fullA + 8 * p);
        if (p == 4 || p == 5) { mbar_expect_tx(fullB + 8 * (p + 2), 25088); bulk_load(sm + K4_B + (p - 4) * 25088, wsrc + (p + 2) * 25088, 25088, fullB + 8 * (p + 2)); }
      }
    }
  } else {
    float acc[56];
    constexpr uint64_t dA = desc_hi(1024, 128, 0), dB = desc_hi(128, 1792, 0);
#pragma unroll 1
    for (int p = 0; p < 8; p++) {
      mbar_wait(fullB + 8 * p, 0);
      mbar_wait(fullA + 8 * p, 0);
      if (p == 0) PT(3, 0, 1);
      const uint32_t a = sm + K4_A + (p & 3) * 14336, b = sm + K4_B + (p >= 6 ? p - 6 : p) * 25088;
      wg_fence();
#pragma unroll
      for (int k = 0; k < 7; k++) wgmma_ss_n112<0, 1>(acc, mkdesc(a + k * 2048, dA), mkdesc(b + k * 256, dB), (p | k) != 0);
      wg_commit();
      if (p > 0) { wg_wait<1>(); if (tid == 0) mbar_arrive(done + 8 * (p - 1)); }
    }
    wg_wait<0>();
    fence_regs<56>(acc);
    PT(3, 0, 2);
    mbar_wait(fullX, 0);
    bar_sync(1, 128);
    const int t4 = lane & 3, mj = lane >> 3;
#pragma unroll
    for (int jj = 0; jj < 7; jj++) {
      uint32_t x[4], o[4];
      const int dr = (2 * jj + (mj >> 1)) * 8 + (lane & 7), sc = 2 * warp + (mj & 1);
      ldsm4t(sm + K4_X + dr * 128 + ((sc ^ (dr & 7)) << 4), x[0], x[1], x[2], x[3]);
      const uint32_t g0 = lds32(sm + K4_GB + (8 * jj + t4) * 4), g1 = lds32(sm + K4_GB + (8 * jj + 4 + t4) * 4);
      o[0] = hadd2(x[0], hmul2(g0, pack_bf16(acc[8 * jj], acc[8 * jj + 1])));
      o[1] = hadd2(x[1], hmul2(g0, pack_bf16(acc[8 * jj + 2], acc[8 * jj + 3])));
      o[2] = hadd2(x[2], hmul2(g1, pack_bf16(acc[8 * jj + 4], acc[8 * jj + 5])));
      o[3] = hadd2(x[3], hmul2(g1, pack_bf16(acc[8 * jj + 6], acc[8 * jj + 7])));
      stsm4(sm + K4_A + (16 * warp + (mj & 1) * 8 + (lane & 7)) * 224 + (2 * jj + (mj >> 1)) * 16, o[0], o[1], o[2], o[3]);
    }
    fence_async_smem();
    bar_sync(1, 128);
    if (tid == 0) { tma_store_2d(&tm_out, sm + K4_A, c * 112, Rt * 64); bulk_commit(); bulk_wait_read(); }
    PT(3, 0, 3);
  }
}

typedef CUresult (*PFN_tmEncode)(CUtensorMap*, CUtensorMapDataType, cuuint32_t, void*, const cuuint64_t*, const cuuint64_t*, const cuuint32_t*, const cuuint32_t*,
                                 CUtensorMapInterleave, CUtensorMapSwizzle, CUtensorMapL2promotion, CUtensorMapFloatOOBfill);
static CUtensorMap make_map(PFN_tmEncode enc, const void* base, uint64_t inner, uint64_t outer, uint32_t bi, uint32_t bo, CUtensorMapSwizzle sw) {
  CUtensorMap m; cuuint64_t gd[2] = {inner, outer}; cuuint64_t gs[1] = {inner * 2}; cuuint32_t bd[2] = {bi, bo}; cuuint32_t es[2] = {1, 1};
  enc(&m, CU_TENSOR_MAP_DATA_TYPE_BFLOAT16, 2, (void*)base, gd, gs, bd, es, CU_TENSOR_MAP_INTERLEAVE_NONE, sw, CU_TENSOR_MAP_L2_PROMOTION_L2_256B, CU_TENSOR_MAP_FLOAT_OOB_FILL_NONE);
  return m;
}
template <typename... KA, typename... A>
static void launch(void (*k)(KA...), int grid, int block, int smem, bool pdl, A... args) {
  cudaLaunchConfig_t cfg = {};
  cfg.gridDim = dim3(grid); cfg.blockDim = dim3(block); cfg.dynamicSmemBytes = smem; cfg.stream = cudaStreamPerThread;
  cudaLaunchAttribute at[1];
  at[0].id = cudaLaunchAttributeProgrammaticStreamSerialization; at[0].val.programmaticStreamSerializationAllowed = 1;
  cfg.attrs = at; cfg.numAttrs = pdl ? 1 : 0;
  cudaLaunchKernelEx(&cfg, k, args...);
}

extern "C" void kernel_launch(void* const* d_in, const int* in_sizes, int n_in, void* d_out, int out_size) {
  static PFN_tmEncode enc = nullptr;
  static void* p_x1T;
  if (!enc) {
    void* p = nullptr; cudaDriverEntryPointQueryResult q;
    cudaGetDriverEntryPoint("cuTensorMapEncodeTiled", &p, cudaEnableDefault, &q);
    enc = (PFN_tmEncode)p;
    cudaGetSymbolAddress(&p_x1T, g_x1T);
    cudaFuncSetAttribute(k1_conv, cudaFuncAttributeMaxDynamicSharedMemorySize, K1_SMEM);
    cudaFuncSetAttribute(kb_gemm12, cudaFuncAttributeMaxDynamicSharedMemorySize, KB_SMEM);
    cudaFuncSetAttribute(k4_gemm3, cudaFuncAttributeMaxDynamicSharedMemorySize, K4_SMEM);
  }
  K1Args a;
  a.u = (const bf16*)d_in[0]; a.Are = (const bf16*)d_in[1]; a.Aim = (const bf16*)d_in[2]; a.Bre = (const bf16*)d_in[3]; a.Bim = (const bf16*)d_in[4];
  a.Cre = (const bf16*)d_in[5]; a.Cim = (const bf16*)d_in[6]; a.logdt = (const bf16*)d_in[7]; a.dskip = (const bf16*)d_in[8];
  a.w_out = (const bf16*)d_in[13]; a.c = (const bf16*)d_in[14]; a.w_sp = (const bf16*)d_in[11]; a.w_mod = (const bf16*)d_in[15]; a.w_in = (const bf16*)d_in[10];
  const CUtensorMap tm_x1a = make_map(enc, p_x1T, L_, D_, 64, 64, CU_TENSOR_MAP_SWIZZLE_128B);
  const CUtensorMap tm_wsp = make_map(enc, d_in[11], L_, L_, 64, 128, CU_TENSOR_MAP_SWIZZLE_128B);
  const CUtensorMap tm_x1 = make_map(enc, p_x1T, L_, D_, 64, 112, CU_TENSOR_MAP_SWIZZLE_128B);
  const CUtensorMap tm_out = make_map(enc, d_out, D_, L_, 112, 64, CU_TENSOR_MAP_SWIZZLE_NONE);
  const CUtensorMap tm_wmod1 = make_map(enc, d_in[15], 6 * D_, D_, 56, 224, CU_TENSOR_MAP_SWIZZLE_NONE);
  const CUtensorMap tm_wmod2 = make_map(enc, d_in[15], 6 * D_, D_, 112, 224, CU_TENSOR_MAP_SWIZZLE_NONE);
  const CUtensorMap tm_win = make_map(enc, d_in[10], F_, D_, 112, 224, CU_TENSOR_MAP_SWIZZLE_NONE);
  launch(k1_conv, 128, 512, K1_SMEM, false, a, tm_wmod1, tm_wmod2, tm_win);
  launch(kb_gemm12, 128, 384, KB_SMEM, true, tm_x1a, tm_wsp, (const bf16*)d_in[12]);
  launch(k4_gemm3, 128, 160, K4_SMEM, true, tm_x1, tm_out);
}
```

```cpp
#include <cuda_runtime.h>
#include <cuda.h>
#include <cuda_bf16.h>
#include <stdint.h>

typedef __nv_bfloat16 bf16;
typedef __nv_bfloat162 bf162;

constexpr int L_ = 2048, D_ = 448, NM_ = 256, F_ = 1792, FH_ = 896;

__device__ __align__(16) uint2 g_xstat[L_ * 8];
__device__ __align__(16) uint2 g_stat1[L_];
__device__ __align__(128) uint2 g_uT[112 * L_];
__device__ __align__(16) uint32_t g_mod[6 * D_];
__device__ __align__(1024) bf16 g_x1T[D_ * L_];
__device__ __align__(1024) uint8_t g_wimg[16 * 7 * 14336];
__device__ __align__(1024) uint8_t g_waug[16 * 3584];
__device__ __align__(1024) uint8_t g_woimg[4 * 8 * 25088];
__device__ __align__(16) uint2 g_zstat[L_ * 8];
__device__ unsigned int g_zcnt[64 * 32];
__device__ unsigned int g_pcnt[33 * 32];
__device__ __align__(1024) uint8_t g_z2img[32 * 4 * 28672];
__device__ __align__(1024) uint8_t g_pimg[32 * 8 * 14336];
__device__ unsigned int g_epoch;

__device__ __forceinline__ uint32_t smem_u32(const void* p) { return (uint32_t)__cvta_generic_to_shared(p); }
__device__ __forceinline__ void mbar_init(uint32_t bar, uint32_t cnt) { asm volatile("mbarrier.init.shared::cta.b64 [%0], %1;" ::"r"(bar), "r"(cnt) : "memory"); }
__device__ __forceinline__ void mbar_expect_tx(uint32_t bar, uint32_t bytes) { asm volatile("mbarrier.arrive.expect_tx.shared::cta.b64 _, [%0], %1;" ::"r"(bar), "r"(bytes) : "memory"); }
__device__ __forceinline__ void mbar_arrive(uint32_t bar) { asm volatile("mbarrier.arrive.shared::cta.b64 _, [%0];" ::"r"(bar) : "memory"); }
__device__ __forceinline__ uint32_t mapa(uint32_t addr, uint32_t cta) { uint32_t r; asm volatile("mapa.shared::cluster.u32 %0, %1, %2;" : "=r"(r) : "r"(addr), "r"(cta)); return r; }
__device__ __forceinline__ void mbar_arrive_remote(uint32_t raddr) { asm volatile("mbarrier.arrive.shared::cluster.b64 _, [%0];" ::"r"(raddr) : "memory"); }
__device__ __forceinline__ void mbar_wait(uint32_t bar, uint32_t parity) {
  asm volatile("{\n.reg .pred p;\n.reg .u32 c;\nmov.u32 c, 0;\nWL:\nmbarrier.try_wait.parity.shared::cta.b64 p, [%0], %1;\n@p bra WD;\nadd.u32 c, c, 1;\n"
               "setp.lt.u32 p, c, 4194304;\n@p bra WL;\ntrap;\nWD:\n}\n" ::"r"(bar), "r"(parity) : "memory");
}
__device__ __forceinline__ void tma_load_2d(uint32_t dst, const void* tmap, int c0, int c1, uint32_t bar) {
  asm volatile("cp.async.bulk.tensor.2d.shared::cluster.global.mbarrier::complete_tx::bytes [%0], [%1, {%3, %4}], [%2];" ::"r"(dst), "l"(tmap), "r"(bar), "r"(c0), "r"(c1) : "memory");
}
__device__ __forceinline__ void tma_load_3d(uint32_t dst, const void* tmap, int c0, int c1, int c2, uint32_t bar) {
  asm volatile("cp.async.bulk.tensor.3d.shared::cluster.global.mbarrier::complete_tx::bytes [%0], [%1, {%3, %4, %5}], [%2];" ::"r"(dst), "l"(tmap), "r"(bar), "r"(c0), "r"(c1), "r"(c2) : "memory");
}
__device__ __forceinline__ void tma_load_2d_mc(uint32_t dst, const void* tmap, int c0, int c1, uint32_t bar, uint16_t mask) {
  asm volatile("cp.async.bulk.tensor.2d.shared::cluster.global.mbarrier::complete_tx::bytes.multicast::cluster [%0], [%1, {%3, %4}], [%2], %5;" ::"r"(dst), "l"(tmap), "r"(bar), "r"(c0), "r"(c1), "h"(mask) : "memory");
}
__device__ __forceinline__ void tmap_prefetch(const void* tmap) { asm volatile("prefetch.tensormap [%0];" ::"l"(tmap) : "memory"); }
__device__ __forceinline__ void tma_store_2d(const void* tmap, uint32_t src, int c0, int c1) {
  asm volatile("cp.async.bulk.tensor.2d.global.shared::cta.bulk_group [%0, {%2, %3}], [%1];" ::"l"(tmap), "r"(src), "r"(c0), "r"(c1) : "memory");
}
__device__ __forceinline__ void bulk_load(uint32_t dst, const void* src, uint32_t bytes, uint32_t bar) {
  asm volatile("cp.async.bulk.shared::cluster.global.mbarrier::complete_tx::bytes [%0], [%1], %2, [%3];" ::"r"(dst), "l"(src), "r"(bytes), "r"(bar) : "memory");
}
__device__ __forceinline__ void bulk_store(void* dst, uint32_t src, uint32_t bytes) {
  asm volatile("cp.async.bulk.global.shared::cta.bulk_group [%0], [%1], %2;" ::"l"(dst), "r"(src), "r"(bytes) : "memory");
}
__device__ __forceinline__ void l2_prefetch(const void* p, uint32_t bytes) { asm volatile("cp.async.bulk.prefetch.L2.global [%0], %1;" ::"l"(p), "r"(bytes) : "memory"); }
__device__ __forceinline__ void bulk_commit() { asm volatile("cp.async.bulk.commit_group;" ::: "memory"); }
__device__ __forceinline__ void bulk_wait_all() { asm volatile("cp.async.bulk.wait_group 0;" ::: "memory"); }
__device__ __forceinline__ void bulk_wait_read() { asm volatile("cp.async.bulk.wait_group.read 0;" ::: "memory"); }
__device__ __forceinline__ void fence_async_smem() { asm volatile("fence.proxy.async.shared::cta;" ::: "memory"); }
__device__ __forceinline__ void wg_fence() { asm volatile("wgmma.fence.sync.aligned;" ::: "memory"); }
__device__ __forceinline__ void wg_commit() { asm volatile("wgmma.commit_group.sync.aligned;" ::: "memory"); }
template <int N> __device__ __forceinline__ void wg_wait() { asm volatile("wgmma.wait_group.sync.aligned %0;" ::"n"(N) : "memory"); }
template <int N> __device__ __forceinline__ void fence_regs(float* d) {
#pragma unroll
  for (int i = 0; i < N; i++) asm volatile("" : "+f"(d[i])::"memory");
}
__device__ __forceinline__ void bar_sync(int id, int n) { asm volatile("bar.sync %0, %1;" ::"r"(id), "r"(n) : "memory"); }
__device__ __forceinline__ void bar_arrive(int id, int n) { asm volatile("bar.arrive %0, %1;" ::"r"(id), "r"(n) : "memory"); }
__device__ __forceinline__ void pdl_wait() { asm volatile("griddepcontrol.wait;" ::: "memory"); }
__device__ __forceinline__ void pdl_launch() { asm volatile("griddepcontrol.launch_dependents;" ::: "memory"); }
__device__ __forceinline__ constexpr uint64_t desc_hi(uint32_t lbo, uint32_t sbo, uint32_t swz) {
  return ((uint64_t)(lbo >> 4) << 16) | ((uint64_t)(sbo >> 4) << 32) | ((uint64_t)swz << 62);
}
__device__ __forceinline__ uint64_t mkdesc(uint32_t addr, uint64_t hi) { return hi | (uint64_t)((addr & 0x3FFFFu) >> 4); }
__device__ __forceinline__ uint32_t pack_bf16(float lo, float hi) { uint32_t r; asm("cvt.rn.bf16x2.f32 %0, %1, %2;" : "=r"(r) : "f"(hi), "f"(lo)); return r; }
__device__ __forceinline__ float bf_lo(uint32_t v) { return __uint_as_float(v << 16); }
__device__ __forceinline__ float bf_hi(uint32_t v) { return __uint_as_float(v & 0xFFFF0000u); }
__device__ __forceinline__ float bf_round(float x) { return __bfloat162float(__float2bfloat16_rn(x)); }
__device__ __forceinline__ uint32_t hmul2(uint32_t a, uint32_t b) { uint32_t r; asm("mul.rn.bf16x2 %0, %1, %2;" : "=r"(r) : "r"(a), "r"(b)); return r; }
__device__ __forceinline__ uint32_t hadd2(uint32_t a, uint32_t b) { uint32_t r; asm("add.rn.bf16x2 %0, %1, %2;" : "=r"(r) : "r"(a), "r"(b)); return r; }
__device__ __forceinline__ uint32_t hsub2(uint32_t a, uint32_t b) { uint32_t r; asm("sub.rn.bf16x2 %0, %1, %2;" : "=r"(r) : "r"(a), "r"(b)); return r; }
__device__ __forceinline__ uint32_t prmt(uint32_t a, uint32_t b, uint32_t s) { uint32_t r; asm("prmt.b32 %0, %1, %2, %3;" : "=r"(r) : "r"(a), "r"(b), "r"(s)); return r; }
__device__ __forceinline__ uint4 lds128(uint32_t a) { uint4 v; asm volatile("ld.shared.v4.u32 {%0,%1,%2,%3}, [%4];" : "=r"(v.x), "=r"(v.y), "=r"(v.z), "=r"(v.w) : "r"(a) : "memory"); return v; }
__device__ __forceinline__ float4 lds128f(uint32_t a) { float4 v; asm volatile("ld.shared.v4.f32 {%0,%1,%2,%3}, [%4];" : "=f"(v.x), "=f"(v.y), "=f"(v.z), "=f"(v.w) : "r"(a) : "memory"); return v; }
__device__ __forceinline__ uint2 lds64(uint32_t a) { uint2 v; asm volatile("ld.shared.v2.u32 {%0,%1}, [%2];" : "=r"(v.x), "=r"(v.y) : "r"(a) : "memory"); return v; }
__device__ __forceinline__ float2 lds64f(uint32_t a) { float2 v; asm volatile("ld.shared.v2.f32 {%0,%1}, [%2];" : "=f"(v.x), "=f"(v.y) : "r"(a) : "memory"); return v; }
__device__ __forceinline__ uint32_t lds32(uint32_t a) { uint32_t v; asm volatile("ld.shared.u32 %0, [%1];" : "=r"(v) : "r"(a) : "memory"); return v; }
__device__ __forceinline__ float lds32f(uint32_t a) { float v; asm volatile("ld.shared.f32 %0, [%1];" : "=f"(v) : "r"(a) : "memory"); return v; }
__device__ __forceinline__ uint32_t lds16(uint32_t a) { uint16_t v; asm volatile("ld.shared.u16 %0, [%1];" : "=h"(v) : "r"(a) : "memory"); return v; }
__device__ __forceinline__ void sts128(uint32_t a, uint4 v) { asm volatile("st.shared.v4.u32 [%0], {%1,%2,%3,%4};" ::"r"(a), "r"(v.x), "r"(v.y), "r"(v.z), "r"(v.w) : "memory"); }
__device__ __forceinline__ void sts64(uint32_t a, uint32_t x, uint32_t y) { asm volatile("st.shared.v2.u32 [%0], {%1,%2};" ::"r"(a), "r"(x), "r"(y) : "memory"); }
__device__ __forceinline__ void sts64f(uint32_t a, float x, float y) { asm volatile("st.shared.v2.f32 [%0], {%1,%2};" ::"r"(a), "f"(x), "f"(y) : "memory"); }
__device__ __forceinline__ void sts32(uint32_t a, uint32_t x) { asm volatile("st.shared.u32 [%0], %1;" ::"r"(a), "r"(x) : "memory"); }
__device__ __forceinline__ void sts16(uint32_t a, uint32_t x) { asm volatile("st.shared.u16 [%0], %1;" ::"r"(a), "h"((uint16_t)x) : "memory"); }
__device__ __forceinline__ void sts32f(uint32_t a, float x) { asm volatile("st.shared.f32 [%0], %1;" ::"r"(a), "f"(x) : "memory"); }
__device__ __forceinline__ void ldsm4(uint32_t a, uint32_t& r0, uint32_t& r1, uint32_t& r2, uint32_t& r3) {
  asm volatile("ldmatrix.sync.aligned.m8n8.x4.shared.b16 {%0,%1,%2,%3}, [%4];" : "=r"(r0), "=r"(r1), "=r"(r2), "=r"(r3) : "r"(a) : "memory");
}
__device__ __forceinline__ void ldsm4t(uint32_t a, uint32_t& r0, uint32_t& r1, uint32_t& r2, uint32_t& r3) {
  asm volatile("ldmatrix.sync.aligned.m8n8.x4.trans.shared.b16 {%0,%1,%2,%3}, [%4];" : "=r"(r0), "=r"(r1), "=r"(r2), "=r"(r3) : "r"(a) : "memory");
}
__device__ __forceinline__ void stsm4(uint32_t a, uint32_t r0, uint32_t r1, uint32_t r2, uint32_t r3) {
  asm volatile("stmatrix.sync.aligned.m8n8.x4.shared.b16 [%0], {%1,%2,%3,%4};" ::"r"(a), "r"(r0), "r"(r1), "r"(r2), "r"(r3) : "memory");
}
__device__ __forceinline__ void stsm4t(uint32_t a, uint32_t r0, uint32_t r1, uint32_t r2, uint32_t r3) {
  asm volatile("stmatrix.sync.aligned.m8n8.x4.trans.shared.b16 [%0], {%1,%2,%3,%4};" ::"r"(a), "r"(r0), "r"(r1), "r"(r2), "r"(r3) : "memory");
}
__device__ __forceinline__ void mma16816(float* c, uint32_t a0, uint32_t a1, uint32_t a2, uint32_t a3, uint32_t b0, uint32_t b1) {
  asm volatile("mma.sync.aligned.m16n8k16.row.col.f32.bf16.bf16.f32 {%0,%1,%2,%3}, {%4,%5,%6,%7}, {%8,%9}, {%0,%1,%2,%3};"
               : "+f"(c[0]), "+f"(c[1]), "+f"(c[2]), "+f"(c[3]) : "r"(a0), "r"(a1), "r"(a2), "r"(a3), "r"(b0), "r"(b1));
}
__device__ __forceinline__ uint4 ldg128_nc(const void* p) { uint4 v; asm volatile("ld.global.nc.L1::no_allocate.v4.u32 {%0,%1,%2,%3}, [%4];" : "=r"(v.x), "=r"(v.y), "=r"(v.z), "=r"(v.w) : "l"(p)); return v; }
__device__ __forceinline__ uint2 ldg64_nc(const void* p) { uint2 v; asm volatile("ld.global.nc.L1::no_allocate.v2.u32 {%0,%1}, [%2];" : "=r"(v.x), "=r"(v.y) : "l"(p)); return v; }
__device__ __forceinline__ uint32_t ldg32_nc(const void* p) { uint32_t v; asm volatile("ld.global.nc.u32 %0, [%1];" : "=r"(v) : "l"(p)); return v; }
__device__ __forceinline__ uint32_t ldg16_nc(const void* p) { uint16_t v; asm volatile("ld.global.nc.u16 %0, [%1];" : "=h"(v) : "l"(p)); return v; }
__device__ __forceinline__ uint4 ldg128_cg(const void* p) { uint4 v; asm volatile("ld.global.cg.v4.u32 {%0,%1,%2,%3}, [%4];" : "=r"(v.x), "=r"(v.y), "=r"(v.z), "=r"(v.w) : "l"(p) : "memory"); return v; }
__device__ __forceinline__ void st_rlx64x(void* p, uint32_t x, uint32_t y) { asm volatile("st.relaxed.gpu.global.b64 [%0], %1;" ::"l"(p), "l"((uint64_t)x | ((uint64_t)y << 32)) : "memory"); }
__device__ __forceinline__ void st_rlx32(void* p, uint32_t x) { asm volatile("st.relaxed.gpu.global.u32 [%0], %1;" ::"l"(p), "r"(x) : "memory"); }
__device__ __forceinline__ uint32_t ld_rlx32(const void* p) { uint32_t v; asm volatile("ld.relaxed.gpu.global.u32 %0, [%1];" : "=r"(v) : "l"(p) : "memory"); return v; }
__device__ __forceinline__ uint2 ld_rlx64(const void* p) {
  uint64_t a; asm volatile("ld.relaxed.gpu.global.b64 %0, [%1];" : "=l"(a) : "l"(p) : "memory");
  return make_uint2((uint32_t)a, (uint32_t)(a >> 32));
}
__device__ __forceinline__ uint4 ld_rlx2x64(const void* p) {
  uint64_t a, b; asm volatile("ld.relaxed.gpu.global.v2.b64 {%0,%1}, [%2];" : "=l"(a), "=l"(b) : "l"(p) : "memory");
  return make_uint4((uint32_t)a, (uint32_t)(a >> 32), (uint32_t)b, (uint32_t)(b >> 32));
}
__device__ __forceinline__ float rcp_fast(float x) { float r; asm("rcp.approx.ftz.f32 %0, %1;" : "=f"(r) : "f"(x)); return r; }
__device__ __forceinline__ float ln_den(float var) { float r; asm("sqrt.approx.ftz.f32 %0, %1;" : "=f"(r) : "f"(bf_round(bf_round(var) + 1e-5f))); return bf_round(r); }
__device__ __forceinline__ float ln_rden(float var) { return rcp_fast(ln_den(var)); }
#define PTX2(i)
#define PT(k, role, i)
#define PTX(i)
__device__ __forceinline__ void wgmma_rs_n16(float* d, uint32_t a0, uint32_t a1, uint32_t a2, uint32_t a3, uint64_t db, int sc){
  asm volatile("{\n.reg .pred p;\nsetp.ne.b32 p, %13, 0;\nwgmma.mma_async.sync.aligned.m64n16k16.f32.bf16.bf16 {%0,%1,%2,%3,%4,%5,%6,%7}, {%8,%9,%10,%11}, %12, p, 1, 1, 0;\n}\n"
   : "+f"(d[0]),"+f"(d[1]),"+f"(d[2]),"+f"(d[3]),"+f"(d[4]),"+f"(d[5]),"+f"(d[6]),"+f"(d[7]) : "r"(a0), "r"(a1), "r"(a2), "r"(a3), "l"(db), "r"(sc));
}
__device__ __forceinline__ void wgmma_rs_n24(float* d, uint32_t a0, uint32_t a1, uint32_t a2, uint32_t a3, uint64_t db, int sc){
  asm volatile("{\n.reg .pred p;\nsetp.ne.b32 p, %17, 0;\nwgmma.mma_async.sync.aligned.m64n24k16.f32.bf16.bf16 {%0,%1,%2,%3,%4,%5,%6,%7,%8,%9,%10,%11}, {%12,%13,%14,%15}, %16, p, 1, 1, 0;\n}\n"
   : "+f"(d[0]),"+f"(d[1]),"+f"(d[2]),"+f"(d[3]),"+f"(d[4]),"+f"(d[5]),"+f"(d[6]),"+f"(d[7]),"+f"(d[8]),"+f"(d[9]),"+f"(d[10]),"+f"(d[11]) : "r"(a0), "r"(a1), "r"(a2), "r"(a3), "l"(db), "r"(sc));
}
__device__ __forceinline__ void wgmma_rs_n32(float* d, uint32_t a0, uint32_t a1, uint32_t a2, uint32_t a3, uint64_t db, int sc){
  asm volatile("{\n.reg .pred p;\nsetp.ne.b32 p, %21, 0;\nwgmma.mma_async.sync.aligned.m64n32k16.f32.bf16.bf16 {%0,%1,%2,%3,%4,%5,%6,%7,%8,%9,%10,%11,%12,%13,%14,%15}, {%16,%17,%18,%19}, %20, p, 1, 1, 0;\n}\n"
   : "+f"(d[0]),"+f"(d[1]),"+f"(d[2]),"+f"(d[3]),"+f"(d[4]),"+f"(d[5]),"+f"(d[6]),"+f"(d[7]),"+f"(d[8]),"+f"(d[9]),"+f"(d[10]),"+f"(d[11]),"+f"(d[12]),"+f"(d[13]),"+f"(d[14]),"+f"(d[15]) : "r"(a0), "r"(a1), "r"(a2), "r"(a3), "l"(db), "r"(sc));
}
__device__ __forceinline__ void wgmma_rs_n112_tb(float* d, uint32_t a0, uint32_t a1, uint32_t a2, uint32_t a3, uint64_t db, int sc){
  asm volatile("{\n.reg .pred p;\nsetp.ne.b32 p, %61, 0;\nwgmma.mma_async.sync.aligned.m64n112k16.f32.bf16.bf16 {%0,%1,%2,%3,%4,%5,%6,%7,%8,%9,%10,%11,%12,%13,%14,%15,%16,%17,%18,%19,%20,%21,%22,%23,%24,%25,%26,%27,%28,%29,%30,%31,%32,%33,%34,%35,%36,%37,%38,%39,%40,%41,%42,%43,%44,%45,%46,%47,%48,%49,%50,%51,%52,%53,%54,%55}, {%56,%57,%58,%59}, %60, p, 1, 1, 1;\n}\n"
   : "+f"(d[0]),"+f"(d[1]),"+f"(d[2]),"+f"(d[3]),"+f"(d[4]),"+f"(d[5]),"+f"(d[6]),"+f"(d[7]),"+f"(d[8]),"+f"(d[9]),"+f"(d[10]),"+f"(d[11]),"+f"(d[12]),"+f"(d[13]),"+f"(d[14]),"+f"(d[15]),"+f"(d[16]),"+f"(d[17]),"+f"(d[18]),"+f"(d[19]),"+f"(d[20]),"+f"(d[21]),"+f"(d[22]),"+f"(d[23]),"+f"(d[24]),"+f"(d[25]),"+f"(d[26]),"+f"(d[27]),"+f"(d[28]),"+f"(d[29]),"+f"(d[30]),"+f"(d[31]),"+f"(d[32]),"+f"(d[33]),"+f"(d[34]),"+f"(d[35]),"+f"(d[36]),"+f"(d[37]),"+f"(d[38]),"+f"(d[39]),"+f"(d[40]),"+f"(d[41]),"+f"(d[42]),"+f"(d[43]),"+f"(d[44]),"+f"(d[45]),"+f"(d[46]),"+f"(d[47]),"+f"(d[48]),"+f"(d[49]),"+f"(d[50]),"+f"(d[51]),"+f"(d[52]),"+f"(d[53]),"+f"(d[54]),"+f"(d[55]) : "r"(a0), "r"(a1), "r"(a2), "r"(a3), "l"(db), "r"(sc));
}
template<int TA,int TB> __device__ __forceinline__ void wgmma_ss_n112(float* d, uint64_t da, uint64_t db, int sc){
  asm volatile("{\n.reg .pred p;\nsetp.ne.b32 p, %58, 0;\nwgmma.mma_async.sync.aligned.m64n112k16.f32.bf16.bf16 {%0,%1,%2,%3,%4,%5,%6,%7,%8,%9,%10,%11,%12,%13,%14,%15,%16,%17,%18,%19,%20,%21,%22,%23,%24,%25,%26,%27,%28,%29,%30,%31,%32,%33,%34,%35,%36,%37,%38,%39,%40,%41,%42,%43,%44,%45,%46,%47,%48,%49,%50,%51,%52,%53,%54,%55}, %56, %57, p, 1, 1, %59, %60;\n}\n"
   : "+f"(d[0]),"+f"(d[1]),"+f"(d[2]),"+f"(d[3]),"+f"(d[4]),"+f"(d[5]),"+f"(d[6]),"+f"(d[7]),"+f"(d[8]),"+f"(d[9]),"+f"(d[10]),"+f"(d[11]),"+f"(d[12]),"+f"(d[13]),"+f"(d[14]),"+f"(d[15]),"+f"(d[16]),"+f"(d[17]),"+f"(d[18]),"+f"(d[19]),"+f"(d[20]),"+f"(d[21]),"+f"(d[22]),"+f"(d[23]),"+f"(d[24]),"+f"(d[25]),"+f"(d[26]),"+f"(d[27]),"+f"(d[28]),"+f"(d[29]),"+f"(d[30]),"+f"(d[31]),"+f"(d[32]),"+f"(d[33]),"+f"(d[34]),"+f"(d[35]),"+f"(d[36]),"+f"(d[37]),"+f"(d[38]),"+f"(d[39]),"+f"(d[40]),"+f"(d[41]),"+f"(d[42]),"+f"(d[43]),"+f"(d[44]),"+f"(d[45]),"+f"(d[46]),"+f"(d[47]),"+f"(d[48]),"+f"(d[49]),"+f"(d[50]),"+f"(d[51]),"+f"(d[52]),"+f"(d[53]),"+f"(d[54]),"+f"(d[55]) : "l"(da), "l"(db), "r"(sc), "n"(TA), "n"(TB));
}
template<int TA,int TB> __device__ __forceinline__ void wgmma_ss_n224(float* d, uint64_t da, uint64_t db, int sc){
  asm volatile("{\n.reg .pred p;\nsetp.ne.b32 p, %114, 0;\nwgmma.mma_async.sync.aligned.m64n224k16.f32.bf16.bf16 {%0,%1,%2,%3,%4,%5,%6,%7,%8,%9,%10,%11,%12,%13,%14,%15,%16,%17,%18,%19,%20,%21,%22,%23,%24,%25,%26,%27,%28,%29,%30,%31,%32,%33,%34,%35,%36,%37,%38,%39,%40,%41,%42,%43,%44,%45,%46,%47,%48,%49,%50,%51,%52,%53,%54,%55,%56,%57,%58,%59,%60,%61,%62,%63,%64,%65,%66,%67,%68,%69,%70,%71,%72,%73,%74,%75,%76,%77,%78,%79,%80,%81,%82,%83,%84,%85,%86,%87,%88,%89,%90,%91,%92,%93,%94,%95,%96,%97,%98,%99,%100,%101,%102,%103,%104,%105,%106,%107,%108,%109,%110,%111}, %112, %113, p, 1, 1, %115, %116;\n}\n"
   : "+f"(d[0]),"+f"(d[1]),"+f"(d[2]),"+f"(d[3]),"+f"(d[4]),"+f"(d[5]),"+f"(d[6]),"+f"(d[7]),"+f"(d[8]),"+f"(d[9]),"+f"(d[10]),"+f"(d[11]),"+f"(d[12]),"+f"(d[13]),"+f"(d[14]),"+f"(d[15]),"+f"(d[16]),"+f"(d[17]),"+f"(d[18]),"+f"(d[19]),"+f"(d[20]),"+f"(d[21]),"+f"(d[22]),"+f"(d[23]),"+f"(d[24]),"+f"(d[25]),"+f"(d[26]),"+f"(d[27]),"+f"(d[28]),"+f"(d[29]),"+f"(d[30]),"+f"(d[31]),"+f"(d[32]),"+f"(d[33]),"+f"(d[34]),"+f"(d[35]),"+f"(d[36]),"+f"(d[37]),"+f"(d[38]),"+f"(d[39]),"+f"(d[40]),"+f"(d[41]),"+f"(d[42]),"+f"(d[43]),"+f"(d[44]),"+f"(d[45]),"+f"(d[46]),"+f"(d[47]),"+f"(d[48]),"+f"(d[49]),"+f"(d[50]),"+f"(d[51]),"+f"(d[52]),"+f"(d[53]),"+f"(d[54]),"+f"(d[55]),"+f"(d[56]),"+f"(d[57]),"+f"(d[58]),"+f"(d[59]),"+f"(d[60]),"+f"(d[61]),"+f"(d[62]),"+f"(d[63]),"+f"(d[64]),"+f"(d[65]),"+f"(d[66]),"+f"(d[67]),"+f"(d[68]),"+f"(d[69]),"+f"(d[70]),"+f"(d[71]),"+f"(d[72]),"+f"(d[73]),"+f"(d[74]),"+f"(d[75]),"+f"(d[76]),"+f"(d[77]),"+f"(d[78]),"+f"(d[79]),"+f"(d[80]),"+f"(d[81]),"+f"(d[82]),"+f"(d[83]),"+f"(d[84]),"+f"(d[85]),"+f"(d[86]),"+f"(d[87]),"+f"(d[88]),"+f"(d[89]),"+f"(d[90]),"+f"(d[91]),"+f"(d[92]),"+f"(d[93]),"+f"(d[94]),"+f"(d[95]),"+f"(d[96]),"+f"(d[97]),"+f"(d[98]),"+f"(d[99]),"+f"(d[100]),"+f"(d[101]),"+f"(d[102]),"+f"(d[103]),"+f"(d[104]),"+f"(d[105]),"+f"(d[106]),"+f"(d[107]),"+f"(d[108]),"+f"(d[109]),"+f"(d[110]),"+f"(d[111]) : "l"(da), "l"(db), "r"(sc), "n"(TA), "n"(TB));
}

struct KMap { uint32_t v[640]; };
constexpr int kv_ij(int i, int j) { return i * 40 + j; }
constexpr int KV_ZERO = 39;
constexpr int kv_entry(int v) {
  return v < 256 ? kv_ij(v % 8, v / 8)
       : v < 512 ? kv_ij(8 + (v % 8) / 2, (v - 256) / 8)
       : v < 1024 ? kv_ij(12 + 2 * ((v - 512) / 256) + (v % 8) / 4, ((v - 512) % 256) / 8)
       : v < 2048 ? kv_ij(16 + (v - 1024) / 256, ((v - 1024) % 256) / 8)
       : kv_ij(20, 0);
}
constexpr int round_pos(int x) {
  int step = x < 256 ? 1 : x < 512 ? 2 : 4;
  int q = x / step, r = x % step;
  if (step > 1 && (2 * r > step || (2 * r == step && (q & 1)))) q++;
  return q * step;
}
constexpr int z_entry(int z) {
  if (z < 592) { int x = z - 63; return (x >= 0 && x <= 514) ? kv_entry(round_pos(x)) : KV_ZERO; }
  if (z < 720) { int a = z - 592 - 62; return (a >= 1 && a <= 63) ? kv_entry(512 + 8 * a) : KV_ZERO; }
  if (z < 848) { int a = z - 720 - 63; return (a >= 0 && a <= 63) ? kv_entry(516 + 8 * a) : KV_ZERO; }
  int a = z - 848 - 62; return (a >= 1 && a <= 128) ? kv_entry(1024 + 8 * a) : KV_ZERO;
}
constexpr KMap make_kmap() {
  KMap m{};
  for (int w = 0; w < 640; w++) m.v[w] = (uint32_t)z_entry(2 * w) | ((uint32_t)z_entry(2 * w + 1) << 10) | ((uint32_t)z_entry(2 * w + 2) << 20);
  return m;
}
__device__ __align__(16) const KMap g_kmap = make_kmap();

constexpr int K1_TP = 272, K1_TA1 = 16 * K1_TP, K1_TW = K1_TA1 + 21 * K1_TP, K1_TG = 4 * K1_TW;
constexpr int K1_KV = K1_TA1, K1_Z0 = K1_TW + K1_TA1, K1_Z1 = K1_Z0 + 2624, K1_S = 2 * K1_TW, K1_Y0 = 0, K1_Y2 = K1_S + 11520;
constexpr int K1_S5 = 0, K1_S3 = 3456, K1_EO = 6912;
constexpr int K1_H = 4 * K1_TG, K1_HSZ = 5248, K1_CS = 656;
constexpr int K1_U = K1_H + 4 * K1_HSZ, K1_KM = K1_U + 16384, K1_MISC = K1_KM + 10240;
constexpr int K1_AUXR = 4096, K1_AUXB = 20480;
constexpr int K1_SMEM = K1_MISC + 64;
static_assert(K1_Z1 + 2624 <= K1_S && K1_Y2 + 6528 <= K1_TG && K1_Y0 + 8704 <= K1_Z0 && K1_SMEM <= 232448 && K1_AUXB + 3 * 57344 <= K1_SMEM, "");

struct cplx { float r, i; };
__device__ __forceinline__ cplx cmul(cplx a, cplx b) { cplx c; c.r = fmaf(a.r, b.r, -a.i * b.i); c.i = fmaf(a.r, b.i, a.i * b.r); return c; }
__device__ __forceinline__ cplx csq(cplx a) { cplx c; c.r = fmaf(a.r, a.r, -a.i * a.i); c.i = (a.r + a.r) * a.i; return c; }
__device__ __forceinline__ cplx cexp_p(float ar, float ai, float p) {
  float m; asm("ex2.approx.ftz.f32 %0, %1;" : "=f"(m) : "f"(ar * p * 1.4426950408889634f));
  float t = ai * p * 0.15915494309189535f;
  t = (t - rintf(t)) * 6.283185307179586f;
  cplx c; c.r = m * __cosf(t); c.i = m * __sinf(t); return c;
}
__device__ __forceinline__ uint32_t h_chunk(uint32_t hb, int q) { return hb + (7 - (q & 7)) * K1_CS + ((q >> 3) + 9) * 16; }
__device__ __forceinline__ void unpack_rev(uint4 v, float* o) {
  o[7] = bf_lo(v.x); o[6] = bf_hi(v.x); o[5] = bf_lo(v.y); o[4] = bf_hi(v.y);
  o[3] = bf_lo(v.z); o[2] = bf_hi(v.z); o[1] = bf_lo(v.w); o[0] = bf_hi(v.w);
}

#define K1_DLY_M 200
#define K1_DLY_P 800
struct K1Args {
  const bf16 *u, *Are, *Aim, *Bre, *Bim, *Cre, *Cim, *logdt, *dskip, *c, *w_mod;
  const unsigned int* epoch; const uint32_t* kmap; uint2* stat1; uint2* uT; uint32_t* mod;
  const bf16 *w_in, *w_sp;
  bf16* x1T; uint8_t *wimg, *waug;
};

__device__ __forceinline__ void ln1_part(uint4 lo, uint4 hi, uint32_t part, uint2* uT, int cta, int warp, int lane) {
  if (warp < 14) {
    uint2* o = uT + (warp * 8 + (lane & 3) * 2) * L_ + cta * 16 + (lane >> 2);
    o[0] = make_uint2(lo.x, lo.y); o[8] = make_uint2(hi.x, hi.y); o[L_] = make_uint2(lo.z, lo.w); o[L_ + 8] = make_uint2(hi.z, hi.w);
    float cs[4] = {0.f, 0.f, 0.f, 0.f}, ql[4] = {0.f, 0.f, 0.f, 0.f}, qh[4] = {0.f, 0.f, 0.f, 0.f};
    mma16816(cs, lo.x, hi.x, lo.y, hi.y, 0x3F803F80u, 0x3F803F80u);
    mma16816(ql, lo.x, hi.x, lo.y, hi.y, lo.x, lo.y);
    mma16816(qh, lo.x, hi.x, lo.y, hi.y, hi.x, hi.y);
    mma16816(cs, lo.z, hi.z, lo.w, hi.w, 0x3F803F80u, 0x3F803F80u);
    mma16816(ql, lo.z, hi.z, lo.w, hi.w, lo.z, lo.w);
    mma16816(qh, lo.z, hi.z, lo.w, hi.w, hi.z, hi.w);
    const int g = lane >> 2;
    if ((lane & 3) == (g >> 1)) {
      sts64f(part + warp * 128 + g * 8, cs[0], (g & 1) ? ql[1] : ql[0]);
      sts64f(part + warp * 128 + 64 + g * 8, cs[2], (g & 1) ? qh[3] : qh[2]);
    }
    __syncwarp();
    bar_arrive(1, 480);
  }
}
__device__ __forceinline__ void ln1_fin(uint32_t part, uint2* stat, int lane, uint32_t tag) {
  bar_sync(1, 480);
  float2 p[7];
#pragma unroll
  for (int i = 0; i < 7; i++) p[i] = lds64f(part + i * 256 + lane * 8);
  float s = ((p[0].x + p[1].x) + (p[2].x + p[3].x)) + ((p[4].x + p[5].x) + p[6].x);
  float q = ((p[0].y + p[1].y) + (p[2].y + p[3].y)) + ((p[4].y + p[5].y) + p[6].y);
  s += __shfl_xor_sync(~0u, s, 16); q += __shfl_xor_sync(~0u, q, 16);
  const float mean = s * (1.0f / D_), var = fmaxf(fmaf(-mean, mean, q * (1.0f / D_)), 0.f);
  PTX(14);
  asm volatile("fence.acq_rel.gpu;" ::: "memory");
  PTX(15);
  if (lane < 16) st_rlx64x(stat + lane, __float_as_uint(bf_round(mean)) | tag, __float_as_uint(ln_rden(var)));
  __syncwarp();
}

__device__ __forceinline__ uint32_t silu2(uint32_t c2) {
  const float a = bf_lo(c2), b = bf_hi(c2);
  return pack_bf16(a * rcp_fast(1.0f + __expf(-a)), b * rcp_fast(1.0f + __expf(-b)));
}

__device__ __forceinline__ void aux_slab(uint32_t dst, const CUtensorMap* tm, int col, uint32_t bar) {
  mbar_expect_tx(bar, 57344);
  tma_load_2d(dst, tm, col, 0, bar);
  tma_load_2d(dst + 28672, tm, col, 224, bar);
}
__device__ __forceinline__ void k1_aux(const K1Args& a, const CUtensorMap* tm_wmod, const CUtensorMap* tm_win, uint32_t sm,
                                       int tid, int warp, int lane, int cta) {
  const uint32_t bar = sm + 3840, sc = sm, clk0 = clock(), buf = sm + K1_AUXB;
  const int ax = cta - 112, cb = ax * 64, c2 = cb + (ax >= 7 ? 4 : 2) * D_;
  const bool domod = ax < 14;
  uint4 ulo = make_uint4(0, 0, 0, 0), uhi = ulo;
  if (warp < 14) { const bf16* p = a.u + (cta * 16 + (lane >> 2)) * D_ + warp * 32 + (lane & 3) * 8; ulo = ldg128_nc(p); uhi = ldg128_nc(p + 8 * D_); }
  const uint32_t tagraw = ldg32_nc(a.epoch);
  if (warp == 14) {
    if (lane == 0) {
#pragma unroll 1
      for (int i = 0; i < 8; i++) mbar_init(bar + 8 * i, 1);
      asm volatile("fence.mbarrier_init.release.cluster;" ::: "memory");
      tmap_prefetch(tm_wmod); tmap_prefetch(tm_win);
    }
    __syncwarp();
    bar_arrive(2, 512);
    if (lane == 0) {
      while ((uint32_t)clock() - clk0 < K1_DLY_M) {}
      if (domod) aux_slab(buf, tm_wmod, cb, bar);
      mbar_wait(bar + 56, 0);
      if (domod) aux_slab(buf + 57344, tm_wmod, cb + 3 * D_, bar + 8);
      aux_slab(buf + 2 * 57344, tm_win, ax * 112, bar + 16);
      if (domod) { mbar_wait(bar + 40, 0); aux_slab(buf, tm_wmod, c2, bar + 32); mbar_wait(bar + 48, 0); }
      aux_slab(buf + 57344, tm_win, ax * 112 + 64, bar + 24);
    }
    return;
  }
  const uint32_t tag = (tagraw + 1u) & 0xFFFFu;
  if (warp == 15) {
    ln1_fin(sm + 2048, a.stat1 + cta * 16, lane, tag);
    bar_sync(2, 512);
    if (lane == 0) mbar_arrive(bar + 56);
    bar_sync(3, 480);
    if (lane == 0) { asm volatile("fence.acq_rel.gpu;" ::: "memory"); pdl_launch(); }
    PTX(13);
    return;
  }
  uint32_t af[2][2] = {{0u, 0u}, {0u, 0u}}, ag[2][2];
  {
    if (lane < 4) {
      const bf16* q = a.c + warp * 16 + 2 * lane;
      af[0][0] = ldg32_nc(q); af[0][1] = ldg32_nc(q + 8); af[1][0] = ldg32_nc(q + 224); af[1][1] = ldg32_nc(q + 232);
    }
    __syncwarp();
    ln1_part(ulo, uhi, sm + 2048, a.uT, cta, warp, lane);
  }
  af[0][0] = silu2(af[0][0]); af[0][1] = silu2(af[0][1]); af[1][0] = silu2(af[1][0]); af[1][1] = silu2(af[1][1]);
  PT(0, warp >> 2, 1);
  bar_sync(2, 512);
#pragma unroll 1
  for (int si = domod ? 0 : 3; si < 5; si++) {
    const int st = (0x32410 >> (4 * si)) & 7;
    const uint32_t red = sm + K1_AUXR + (si & 1) * 8192;
    const bool cs = st == 2 || st == 3;
    if (st == 2) {
      uint32_t vc, it = 0;
      do { vc = ld_rlx32(a.mod + 4 * D_ + tid); if (++it > (1u << 22)) __trap(); } while ((vc & 0xFFFFu) != tag);
      sts16(sc + tid * 2, pack_bf16(1.0f + bf_hi(vc), 0.f));
      bar_sync(4, 448);
      mbar_wait(bar + 16, 0); mbar_wait(bar + 24, 0);
      PT(0, warp >> 2, 5);
      const int nc = (tid % 112) >> 3, rl = (tid / 112) * 8 + (tid & 7);
      uint32_t src = buf + (nc < 8 ? 2 * 57344 : 57344) + rl * 128 + (((nc ^ tid) & 7) << 4), ss = sc + rl * 2;
      uint8_t* dst = a.wimg + ax * 7 * 14336 + nc * 1024 + rl * 16;
#pragma unroll 1
      for (int i = 0; i < 7; i++, src += 64 * 128, ss += 128, dst += 14336) {
        const uint4 v0 = lds128(src), v1 = lds128(src + 32 * 128);
        const uint32_t m0 = lds16(ss) * 0x10001u, m1 = lds16(ss + 64) * 0x10001u;
        *(uint4*)dst = make_uint4(hmul2(v0.x, m0), hmul2(v0.y, m0), hmul2(v0.z, m0), hmul2(v0.w, m0));
        *(uint4*)(dst + 512) = make_uint4(hmul2(v1.x, m1), hmul2(v1.y, m1), hmul2(v1.z, m1), hmul2(v1.w, m1));
      }
      bar_arrive(3, 480);
      PT(0, warp >> 2, 6);
      if (tid < 168) *(uint4*)(a.waug + ax * 3584 + (tid / 12) * 256 + 64 + (tid % 12) * 16) = make_uint4(0u, 0u, 0u, 0u);
      ag[0][0] = ag[0][1] = ag[1][0] = ag[1][1] = 0u;
      if (lane < 4) {
        const uint32_t k = sc + (warp * 16 + 2 * lane) * 2;
        ag[0][0] = lds32(k); ag[0][1] = lds32(k + 16); ag[1][0] = lds32(k + 448); ag[1][1] = lds32(k + 464);
      } else if (lane < 8) {
#pragma unroll
        for (int i = 0; i < 2; i++) {
          const int k = warp * 16 + 224 * i + 2 * (lane - 4);
          uint2 v0, v1;
          it = 0;
          do {
            v0 = ld_rlx64(a.mod + 3 * D_ + k); v1 = ld_rlx64(a.mod + 3 * D_ + k + 8);
            if (++it > (1u << 22)) __trap();
          } while (((v0.x ^ tag) | (v0.y ^ tag) | (v1.x ^ tag) | (v1.y ^ tag)) & 0xFFFFu);
          ag[i][0] = prmt(v0.x, v0.y, 0x7632); ag[i][1] = prmt(v1.x, v1.y, 0x7632);
        }
      }
      __syncwarp();
    }
    mbar_wait(bar + 8 * st, 0);
    if (st == 0) PT(0, warp >> 2, 3);
    {
      const uint32_t base = buf + ((0x01210 >> (4 * st)) & 3) * 57344 + (warp * 16 + (lane & 7) + (lane >> 4) * 8) * 128;
      float acc[4][4];
      uint32_t b[2][4][4];
#pragma unroll
      for (int n2 = 0; n2 < 4; n2++) {
        const uint32_t ad = base + (((2 * n2 + ((lane >> 3) & 1)) ^ (lane & 7)) << 4);
        ldsm4t(ad, b[0][n2][0], b[0][n2][1], b[0][n2][2], b[0][n2][3]); ldsm4t(ad + 28672, b[1][n2][0], b[1][n2][1], b[1][n2][2], b[1][n2][3]);
      }
      const uint32_t v00 = cs ? ag[0][0] : af[0][0], v01 = cs ? ag[0][1] : af[0][1], v10 = cs ? ag[1][0] : af[1][0], v11 = cs ? ag[1][1] : af[1][1];
#pragma unroll
      for (int n = 0; n < 4; n++) {
        acc[n][0] = acc[n][1] = acc[n][2] = acc[n][3] = 0.f;
        mma16816(acc[n], b[0][n][0], b[0][n][1], b[0][n][2], b[0][n][3], v00, v01);
        mma16816(acc[n], b[1][n][0], b[1][n][1], b[1][n][2], b[1][n][3], v10, v11);
      }
      if (!(lane & 3)) {
#pragma unroll
        for (int n = 0; n < 4; n++) {
          const uint32_t o = red + (warp * 64 + n * 16 + (lane >> 2)) * 4;
          sts32f(o, acc[n][0]); sts32f(o + 32, acc[n][2]); sts32f(o + 4096, acc[n][1]); sts32f(o + 4096 + 32, acc[n][3]);
        }
      }
    }
    bar_sync(4, 448);
    if (st < 2 && tid == 128) mbar_arrive(bar + 40 + 8 * st);
    if (tid < (cs ? 128 : 64)) {
      float v[14];
#pragma unroll
      for (int r = 0; r < 14; r++) v[r] = lds32f(red + (tid >> 6) * 4096 + (r * 64 + (tid & 63)) * 4);
      const float x = (((v[0] + v[1]) + (v[2] + v[3])) + ((v[4] + v[5]) + (v[6] + v[7]))) + (((v[8] + v[9]) + (v[10] + v[11])) + (v[12] + v[13]));
      const float xr = bf_round(x);
      const int n = (st - 2) * 64 + (tid & 63);
      if (!cs) st_rlx32(a.mod + (st == 4 ? c2 : cb + st * 3 * D_) + tid, __float_as_uint(xr) | tag);
      else if (n < 112) {
        uint16_t* dst = (uint16_t*)(a.waug + ax * 3584 + (n >> 3) * 256 + (tid >> 6) * 32) + (n & 7);
        const uint32_t p = pack_bf16(xr, x - xr);
        dst[0] = (uint16_t)p; dst[8] = (uint16_t)(p >> 16);
      }
    }
    if (st == 0) PT(0, warp >> 2, 2);
    if (st == 1) PT(0, warp >> 2, 4);
  }
  PT(0, warp >> 2, 10);
}

__global__ void __launch_bounds__(512, 1) k1_conv(const K1Args a, const __grid_constant__ CUtensorMap tm_wmod, const __grid_constant__ CUtensorMap tm_win) {
  extern __shared__ __align__(1024) uint8_t smem_raw[];
  const uint32_t sm = smem_u32(smem_raw);
  const int tid = threadIdx.x, warp = __shfl_sync(~0u, tid >> 5, 0), lane = tid & 31, cta = blockIdx.x;
  const int g = lane >> 2, t4 = lane & 3;
  const int d0 = cta * 4;
  const uint32_t s_kv1024 = sm + K1_MISC;
  const int wg = warp >> 2, w4 = warp & 3, t = tid & 127;
  PT(0, wg, 0);
  if (cta >= 112) { k1_aux(a, &tm_wmod, &tm_win, sm, tid, warp, lane, cta); return; }
  const uint32_t clk0 = clock();
  uint4 ulo = make_uint4(0, 0, 0, 0), uhi = ulo;
  if (warp < 14) { const bf16* p = a.u + (cta * 16 + g) * D_ + warp * 32 + t4 * 8; ulo = ldg128_nc(p); uhi = ldg128_nc(p + 8 * D_); }
  const uint32_t tagraw = ldg32_nc(a.epoch);
  const int po = (d0 + wg) * NM_ + 2 * t;
  const uint32_t pAre = ldg32_nc(a.Are + po), pAim = ldg32_nc(a.Aim + po), pBre = ldg32_nc(a.Bre + po), pBim = ldg32_nc(a.Bim + po), pCre = ldg32_nc(a.Cre + po), pCim = ldg32_nc(a.Cim + po);
  const uint32_t ldtr = ldg16_nc(a.logdt + d0 + wg);
  if (tid == 448) pdl_launch();
  if (tid < 4 * 8 * 9) sts128(sm + K1_H + (tid / 72) * K1_HSZ + ((tid % 72) / 9) * K1_CS + (tid % 9) * 16, make_uint4(0, 0, 0, 0));
  if (warp == 14) {
    while ((uint32_t)clock() - clk0 < K1_DLY_P) {}
    if (lane < 4) l2_prefetch((const uint8_t*)a.w_mod + (d0 + lane) * 5376, 1792);
    __syncwarp();
  }
  ln1_part(ulo, uhi, sm + 15 * K1_TW, a.uT, cta, warp, lane);
  if (warp == 15) ln1_fin(sm + 15 * K1_TW, a.stat1 + cta * 16, lane, (tagraw + 1u) & 0xFFFFu);
  PT(0, wg, 13);
  uint32_t km[5];
#pragma unroll
  for (int i = 0; i < 5; i++) km[i] = ldg32_nc(a.kmap + t + 128 * i);
  const float dt = bf_round(expf(bf_lo(ldtr)));
  if (warp == 14 && (pAre ^ pAim ^ pBre ^ pBim ^ pCre ^ pCim) != 0x7FC1FFC3u) {
    if (lane < 4) l2_prefetch((const uint8_t*)a.w_mod + (d0 + lane) * 5376 + 1792, 3584);
    if (lane == 4) l2_prefetch((const uint8_t*)a.w_in + cta * 14336, 14336);
  }
  __syncwarp();
  const uint32_t tag = (tagraw + 1u) & 0xFFFFu;
  PT(0, wg, 1);

  const uint32_t R = sm + wg * K1_TG, ta0 = R + w4 * K1_TW, ta1 = ta0 + K1_TA1;
  float kacc[2][3][4];
#pragma unroll
  for (int i = 0; i < 2; i++)
#pragma unroll
    for (int j = 0; j < 3; j++)
#pragma unroll
      for (int k = 0; k < 4; k++) kacc[i][j][k] = 0.f;
  uint32_t bfr[3][4][4];
  uint4 st01, st23, msa, mca, uqa, uqb;
  {
    cplx E8[2], y[2], E128[2];
#define ST2(base, j, v) sts64((base) + (j) * K1_TP + lane * 8, pack_bf16((v)[0].r, (v)[0].i), pack_bf16((v)[1].r, (v)[1].i))
#define FOR2 _Pragma("unroll") for (int p = 0; p < 2; p++)
    {
      cplx w[2], E1[2], E2[2], E4[2], E256[2], b[2], x[2];
      FOR2 {
        const float ar = dt * (p ? bf_hi(pAre) : bf_lo(pAre)), ai = dt * (p ? bf_hi(pAim) : bf_lo(pAim));
        const cplx db = {dt * (p ? bf_hi(pBre) : bf_lo(pBre)), dt * (p ? bf_hi(pBim) : bf_lo(pBim))};
        const cplx cc = {p ? bf_hi(pCre) : bf_lo(pCre), p ? bf_hi(pCim) : bf_lo(pCim)};
        w[p] = cmul(cc, db);
        w[p].i = -w[p].i;
        E1[p] = cexp_p(ar, -ai, 1.f); E8[p] = cexp_p(ar, ai, 8.f); E128[p] = cexp_p(ar, ai, 128.f);
      }
      FOR2 { E2[p] = csq(E1[p]); E4[p] = csq(E2[p]); E256[p] = csq(E128[p]); E256[p].i = -E256[p].i; b[p] = cmul(w[p], E256[p]); }
      ST2(ta1, 0, w); ST2(ta1, 8, b);
      FOR2 { w[p] = cmul(w[p], E1[p]); x[p] = cmul(b[p], E2[p]); b[p] = cmul(b[p], E256[p]); }
      ST2(ta1, 1, w); ST2(ta1, 9, x); ST2(ta1, 12, b);
      FOR2 { w[p] = cmul(w[p], E1[p]); x[p] = cmul(x[p], E2[p]); y[p] = cmul(b[p], E4[p]); b[p] = cmul(b[p], E256[p]); }
      ST2(ta1, 2, w); ST2(ta1, 10, x); ST2(ta1, 13, y); ST2(ta1, 14, b);
      FOR2 { w[p] = cmul(w[p], E1[p]); x[p] = cmul(x[p], E2[p]); y[p] = cmul(b[p], E4[p]); b[p] = cmul(b[p], E256[p]); }
      ST2(ta1, 3, w); ST2(ta1, 11, x); ST2(ta1, 15, y); ST2(ta1, 16, b);
#pragma unroll
      for (int j = 4; j < 8; j++) {
        FOR2 { w[p] = cmul(w[p], E1[p]); b[p] = cmul(b[p], E256[p]); }
        ST2(ta1, j, w); ST2(ta1, 13 + j, b);
      }
    }
    PT(0, wg, 12);
#pragma unroll
    for (int i = 0; i < 5; i++) sts32(sm + K1_KM + (tid + 512 * i) * 4, km[i]);
    __syncwarp();
    sts64(ta0 + lane * 8, 0x3F80u, 0x3F80u);
    FOR2 y[p] = E8[p];
    ST2(ta0, 1, y);
    const uint32_t bad = ta1 + (lane >> 3) * 16;
#pragma unroll
    for (int j = 2; j < 16; j++) {
      FOR2 y[p] = cmul(y[p], E8[p]);
      ST2(ta0, j, y);
      if (j < 14) {
        const int nt = (j - 2) >> 2, k2 = (j - 2) & 3;
        ldsm4(bad + (nt < 2 ? nt * 8 + (lane & 7) : min(16 + (lane & 7), 20)) * K1_TP + k2 * 64, bfr[nt][k2][0], bfr[nt][k2][1], bfr[nt][k2][2], bfr[nt][k2][3]);
      }
    }
    __syncwarp();
    const uint32_t aad = (lane & 15) * K1_TP + (lane >> 4) * 16;
    FOR2 y[p] = E128[p];
#pragma unroll
    for (int j = 0; j < 16; j++) {
      uint32_t a0, a1, a2, a3;
      if (!(j & 1)) ldsm4(ta0 + aad + j * 16, a0, a1, a2, a3);
      ST2(ta1, j, y);
      if (j < 15) { FOR2 y[p] = cmul(y[p], E8[p]); }
      if (!(j & 1)) {
#pragma unroll
        for (int nt = 0; nt < 3; nt++) mma16816(kacc[0][nt], a0, a1, a2, a3, bfr[nt][j >> 2][(j & 2)], bfr[nt][j >> 2][(j & 2) + 1]);
      }
    }
    PT(0, wg, 3);
    st01 = ld_rlx2x64(a.stat1 + 4 * tid); st23 = ld_rlx2x64(a.stat1 + 4 * tid + 2);
    __syncwarp();
#pragma unroll
    for (int j = 0; j < 8; j++) {
      uint32_t a0, a1, a2, a3;
      ldsm4(ta1 + aad + j * 32, a0, a1, a2, a3);
      if (j < 6) sts64f(ta0 + ((g + 8 * (j & 1)) * 24 + (j >> 1) * 8 + 2 * t4) * 4, kacc[0][j >> 1][2 * (j & 1)], kacc[0][j >> 1][2 * (j & 1) + 1]);
#pragma unroll
      for (int nt = 0; nt < 3; nt++) mma16816(kacc[1][nt], a0, a1, a2, a3, bfr[nt][j >> 1][2 * (j & 1)], bfr[nt][j >> 1][2 * (j & 1) + 1]);
    }
#pragma unroll
    for (int nt = 0; nt < 3; nt++) {
      sts64f(ta0 + ((16 + g) * 24 + nt * 8 + 2 * t4) * 4, kacc[1][nt][0], kacc[1][nt][1]);
      sts64f(ta0 + ((24 + g) * 24 + nt * 8 + 2 * t4) * 4, kacc[1][nt][2], kacc[1][nt][3]);
    }
    for (uint32_t it = 0; ((st01.x ^ tag) | (st01.z ^ tag) | (st23.x ^ tag) | (st23.z ^ tag)) & 0xFFFFu;) {
      st01 = ld_rlx2x64(a.stat1 + 4 * tid); st23 = ld_rlx2x64(a.stat1 + 4 * tid + 2);
      if (++it > (1u << 22)) __trap();
    }
    __syncwarp();
    PT(0, wg, 11);
    uqa = ld_rlx2x64(a.uT + cta * L_ + 4 * tid); uqb = ld_rlx2x64(a.uT + cta * L_ + 4 * tid + 2);
    msa = ld_rlx2x64(a.mod + d0); mca = ld_rlx2x64(a.mod + D_ + d0);
  }
  PT(0, wg, 5);
  bar_sync(2 + wg, 128);
  const uint32_t KV = R + K1_KV;
  {
#pragma unroll
    for (int i = 0; i < 5; i++) km[i] = lds32(sm + K1_KM + (tid + 512 * i) * 4);
    float2 pv[3][4];
#pragma unroll
    for (int i = 0; i < 3; i++)
#pragma unroll
      for (int w = 0; w < 4; w++) pv[i][w] = lds64f(R + w * K1_TW + (t + 128 * i) * 8);
#pragma unroll
    for (int i = 0; i < 3; i++) {
      const float sx = (pv[i][0].x + pv[i][1].x) + (pv[i][2].x + pv[i][3].x), sy = (pv[i][0].y + pv[i][1].y) + (pv[i][2].y + pv[i][3].y);
      const int pr = t + 128 * i, j = pr / 12, ii = 2 * (pr % 12);
      const uint32_t pk = pack_bf16(sx, sy);
      sts16(KV + (ii * 40 + j) * 2, pk); sts16(KV + (ii * 40 + 40 + j) * 2, pk >> 16);
      if (i == 0 && t == 8) sts32f(s_kv1024 + wg * 4, sx);
    }
    if (t == 0) sts16(KV + KV_ZERO * 2, 0u);
  }
  bar_sync(2 + wg, 128);
  uint32_t e0[5], e1[5], e2[5];
#define Z_LOAD(i) { e0[i] = lds16(KV + (km[i] & 1023u) * 2); e1[i] = lds16(KV + ((km[i] >> 10) & 1023u) * 2); e2[i] = lds16(KV + (km[i] >> 20) * 2); }
#define Z_STORE(i) { sts32(R + K1_Z0 + (t + 128 * (i)) * 4, prmt(e0[i], e1[i], 0x5410)); sts32(R + K1_Z1 + (t + 128 * (i)) * 4, prmt(e1[i], e2[i], 0x5410)); }
  Z_LOAD(0) Z_LOAD(1) Z_LOAD(2) Z_LOAD(3) Z_LOAD(4) Z_STORE(0) Z_STORE(1) Z_STORE(2) Z_STORE(3) Z_STORE(4)
  PT(0, wg, 4);
  {
    for (uint32_t it = 0; ((msa.x ^ tag) | (msa.y ^ tag) | (msa.z ^ tag) | (msa.w ^ tag) | (mca.x ^ tag) | (mca.y ^ tag) | (mca.z ^ tag) | (mca.w ^ tag)) & 0xFFFFu;) {
      msa = ld_rlx2x64(a.mod + d0); mca = ld_rlx2x64(a.mod + D_ + d0);
      if (++it > (1u << 22)) __trap();
    }
    __syncwarp();
    PT(0, wg, 2);
    const uint2 uq[4] = {make_uint2(uqa.x, uqa.y), make_uint2(uqa.z, uqa.w), make_uint2(uqb.x, uqb.y), make_uint2(uqb.z, uqb.w)};
    const uint32_t sa01 = prmt(msa.x, msa.y, 0x7632), sa23 = prmt(msa.z, msa.w, 0x7632);
    const uint32_t ca01 = hadd2(prmt(mca.x, mca.y, 0x7632), 0x3F803F80u), ca23 = hadd2(prmt(mca.z, mca.w, 0x7632), 0x3F803F80u);
    const uint32_t mm[4] = {st01.x, st01.z, st23.x, st23.z};
    const float rr[4] = {__uint_as_float(st01.y), __uint_as_float(st01.w), __uint_as_float(st23.y), __uint_as_float(st23.w)};
    uint32_t h01[4], h23[4];
#pragma unroll
    for (int r = 0; r < 4; r++) {
      const uint32_t m2 = prmt(mm[r], mm[r], 0x3232);
      uint32_t dd = hsub2(uq[r].x, m2);
      h01[r] = hadd2(hmul2(pack_bf16(bf_lo(dd) * rr[r], bf_hi(dd) * rr[r]), ca01), sa01);
      dd = hsub2(uq[r].y, m2);
      h23[r] = hadd2(hmul2(pack_bf16(bf_lo(dd) * rr[r], bf_hi(dd) * rr[r]), ca23), sa23);
    }
    const uint32_t ho = h_chunk(sm + K1_H, tid >> 1) + ((tid & 1) ? 0 : 8), uo = sm + K1_U + tid * 8;
    sts64(ho, prmt(h01[3], h01[2], 0x5410), prmt(h01[1], h01[0], 0x5410));
    sts64(ho + K1_HSZ, prmt(h01[3], h01[2], 0x7632), prmt(h01[1], h01[0], 0x7632));
    sts64(ho + 2 * K1_HSZ, prmt(h23[3], h23[2], 0x5410), prmt(h23[1], h23[0], 0x5410));
    sts64(ho + 3 * K1_HSZ, prmt(h23[3], h23[2], 0x7632), prmt(h23[1], h23[0], 0x7632));
    sts64(uo, prmt(uq[0].x, uq[1].x, 0x5410), prmt(uq[2].x, uq[3].x, 0x5410));
    sts64(uo + 4096, prmt(uq[0].x, uq[1].x, 0x7632), prmt(uq[2].x, uq[3].x, 0x7632));
    sts64(uo + 8192, prmt(uq[0].y, uq[1].y, 0x5410), prmt(uq[2].y, uq[3].y, 0x5410));
    sts64(uo + 12288, prmt(uq[0].y, uq[1].y, 0x7632), prmt(uq[2].y, uq[3].y, 0x7632));
  }
  fence_async_smem();
  if (tid >= 480 && tid < 485) l2_prefetch((const uint8_t*)a.w_sp + (size_t)cta * 74880 + (tid - 480) * 14976, cta == 111 && tid == 484 ? 14976 + 2048 : 14976);
  __syncthreads();
  PT(0, wg, 6);
  const uint32_t H = sm + K1_H + wg * K1_HSZ, S = R + K1_S;
  float D0[16], D2[12], D3a[16], D3b[8];
  const uint32_t za = R + ((g & 1) ? K1_Z1 : K1_Z0) + (8 * w4 + (g >> 1) + t4) * 4;
  const uint64_t dH = mkdesc(H + 9 * 16, desc_hi(K1_CS, 128, 0)), dS = mkdesc(S, desc_hi(144, 1152, 0)), dS2 = mkdesc(S + K1_EO, desc_hi(144, 2304, 0));
  uint32_t prev = lds32(za);
  uint32_t sv[8];
#define CONV_LOAD(G)  _Pragma("unroll") for (int i = 0; i < 8; i++) if (4 * (G) + i / 2 < 61) sv[i] = lds32(za + (8 * (G) + i + 1) * 16);
#define CONV_ISSUE(G)                                                                                                        \
  {                                                                                                                          \
    uint32_t cur[8];                                                                                                         \
    _Pragma("unroll") for (int i = 0; i < 8; i++) cur[i] = sv[i];                                                            \
    wg_fence();                                                                                                              \
    _Pragma("unroll") for (int i = 0; i < 4; i++) {                                                                          \
      const int s = 4 * (G) + i;                                                                                             \
      if (s < 61) {                                                                                                          \
        const uint32_t a0 = prev, a1 = cur[2 * i], a3 = cur[2 * i + 1];                                                      \
        if (s < 37) wgmma_rs_n32(D0, a0, a1, a1, a3, dH + (uint64_t)((2 * (s & 3)) * (K1_CS / 16)) - (uint64_t)(s >> 2), s > 0); \
        else if (s < 41) wgmma_rs_n24(D2, a0, a1, a1, a3, dS + (K1_S5 / 16 + (s - 37) * 18), s > 37);                        \
        else if (s < 45) wgmma_rs_n16(D2, a0, a1, a1, a3, dS + (K1_S5 / 16 + (s - 37) * 18), 1);                             \
        else if (s < 49) wgmma_rs_n24(D2, a0, a1, a1, a3, dS + (K1_S3 / 16 + (s - 45) * 18), 1);                             \
        else if (s < 53) wgmma_rs_n16(D2, a0, a1, a1, a3, dS + (K1_S3 / 16 + (s - 45) * 18), 1);                             \
        else if (s < 57) wgmma_rs_n32(D3a, a0, a1, a1, a3, dS + (K1_EO / 16 + (s - 53) * 18), s > 53);                       \
        else wgmma_rs_n16(D3b, a0, a1, a1, a3, dS2 + (s - 53) * 18, s > 57);                                                 \
        prev = a3;                                                                                                           \
      }                                                                                                                      \
    }                                                                                                                        \
    wg_commit();                                                                                                             \
  }
#define CONV_GO(G) CONV_ISSUE(G) CONV_LOAD((G) + 1)
  CONV_LOAD(0)
  {
    const int cb = 8 * (w4 >> 1) + (w4 & 1);
    const int qa = 190 - (64 + 8 * (cb + 2 * t4) + g), qb = 190 - (8 * ((w4 & 1) + 2 * t4) + g);
    const bool second = (w4 >> 1) == (wg & 1);
    const uint32_t ro = S + (2 * ((lane & 7) >> 1)) * 144 + (2 * (lane >> 3) + (lane & 1)) * 16;
    uint4 ra[3], rb[3];
    float hh[24], c[22];
    uint32_t r5[4], r3[4];
    CONV_GO(0)
#pragma unroll
    for (int i = 0; i < 3; i++) ra[i] = lds128(h_chunk(H, qa - 1 + i));
    wg_wait<1>();
    CONV_GO(1)
    wg_wait<1>();
    CONV_GO(2)
    unpack_rev(ra[0], hh); unpack_rev(ra[1], hh + 8); unpack_rev(ra[2], hh + 16);
    c[4] = 0.f;
#pragma unroll
    for (int i = 4; i < 21; i++) c[i + 1] = c[i] + hh[i];
    wg_wait<1>();
    CONV_GO(3)
#pragma unroll
    for (int j = 0; j < 4; j++) {
      r5[j] = pack_bf16(c[11 + 2 * j] - c[6 + 2 * j], c[12 + 2 * j] - c[7 + 2 * j]);
      r3[j] = pack_bf16(c[14 + 2 * j] - c[11 + 2 * j], c[15 + 2 * j] - c[12 + 2 * j]);
    }
    stsm4t(ro + K1_S5 + (8 + cb) * 144, r5[0], r5[1], r5[2], r5[3]);
    stsm4t(ro + K1_S3 + (8 + cb) * 144, r3[0], r3[1], r3[2], r3[3]);
    if (second) {
#pragma unroll
      for (int i = 0; i < 3; i++) rb[i] = lds128(h_chunk(H, qb - 1 + i));
    }
    wg_wait<1>();
    CONV_GO(4)
#pragma unroll
    for (int j = 0; j < 4; j++) {
      const uint32_t s9 = pack_bf16(c[13 + 2 * j] - c[4 + 2 * j], c[14 + 2 * j] - c[5 + 2 * j]);
      const uint32_t s7 = pack_bf16(c[12 + 2 * j] - c[5 + 2 * j], c[13 + 2 * j] - c[6 + 2 * j]);
      r5[j] = (g & 1) ? s7 : s9; r3[j] = (g & 1) ? s9 : s7;
    }
    stsm4t(ro + K1_EO + cb * 144, r5[0], r5[1], r5[2], r5[3]);
    stsm4t(ro + K1_EO + 2304 + cb * 144, r3[0], r3[1], r3[2], r3[3]);
    wg_wait<1>();
    CONV_GO(5)
    if (second) {
      unpack_rev(rb[0], hh); unpack_rev(rb[1], hh + 8); unpack_rev(rb[2], hh + 16);
      c[6] = 0.f;
#pragma unroll
      for (int i = 6; i < 21; i++) c[i + 1] = c[i] + hh[i];
    }
    wg_wait<1>();
    CONV_GO(6)
    if (second) {
#pragma unroll
      for (int j = 0; j < 4; j++) {
        r5[j] = pack_bf16(c[11 + 2 * j] - c[6 + 2 * j], c[12 + 2 * j] - c[7 + 2 * j]);
        r3[j] = pack_bf16(c[14 + 2 * j] - c[11 + 2 * j], c[15 + 2 * j] - c[12 + 2 * j]);
      }
      stsm4t(ro + K1_S5 + (w4 & 1) * 144, r5[0], r5[1], r5[2], r5[3]);
      stsm4t(ro + K1_S3 + (w4 & 1) * 144, r3[0], r3[1], r3[2], r3[3]);
    }
    fence_async_smem();
    wg_wait<1>();
  }
  CONV_GO(7)
  const uint32_t hc0 = h_chunk(H, t);
  const uint4 hm = lds128(h_chunk(H, t - 1)), h0 = lds128(hc0), hp = lds128(h_chunk(H, t + 1));
  const float kv = lds32f(s_kv1024 + wg * 4);
  uint32_t graw = ld_rlx32(a.mod + 2 * D_ + d0 + wg);
  const uint32_t dskr = ldg16_nc(a.dskip + d0 + wg);
  wg_wait<1>();
  CONV_GO(8)
  bar_sync(2 + wg, 128);
  wg_wait<1>();
  CONV_GO(9)
  float f[8];
  {
    float hh[24], c[19];
    unpack_rev(hm, hh); unpack_rev(h0, hh + 8); unpack_rev(hp, hh + 16);
    c[4] = 0.f;
#pragma unroll
    for (int i = 4; i < 18; i++) c[i + 1] = c[i] + hh[i];
    wg_wait<1>();
    CONV_GO(10)
#pragma unroll
    for (int e = 0; e < 8; e++) f[e] = kv * (c[e + 11] - c[e + 4]);
  }
  float f6 = 0.f, f7 = 0.f;
  if (t == 127) { const uint32_t hw = lds32(h_chunk(H, 0) + 12); f6 = kv * bf_hi(hw); f7 = kv * (bf_hi(hw) + bf_lo(hw)); }
  const uint4 h1 = lds128(hc0 + 256);
  wg_wait<1>();
  CONV_GO(11)
  const uint32_t dk2 = dskr * 0x10001u;
  const uint32_t hd[2][4] = {{hmul2(prmt(h0.w, h0.w, 0x1032), dk2), hmul2(prmt(h0.z, h0.z, 0x1032), dk2), hmul2(prmt(h0.y, h0.y, 0x1032), dk2), hmul2(prmt(h0.x, h0.x, 0x1032), dk2)},
                             {hmul2(prmt(h1.w, h1.w, 0x1032), dk2), hmul2(prmt(h1.z, h1.z, 0x1032), dk2), hmul2(prmt(h1.y, h1.y, 0x1032), dk2), hmul2(prmt(h1.x, h1.x, 0x1032), dk2)}};
  wg_wait<1>();
  CONV_GO(12)
  const uint4 u0 = lds128(sm + K1_U + wg * 4096 + t * 16), u1 = lds128(sm + K1_U + wg * 4096 + (t + 128) * 16);
  for (uint32_t it = 0; (graw ^ tag) & 0xFFFFu;) { graw = ld_rlx32(a.mod + 2 * D_ + d0 + wg); if (++it > (1u << 22)) __trap(); }
  __syncwarp();
  wg_wait<1>();
  CONV_GO(13)
  fence_regs<16>(D0);
  {
    const uint32_t y0 = R + K1_Y0 + (136 * t4 + 16 * w4 + g + 4 * (w4 >> 1)) * 4;
#pragma unroll
    for (int j = 0; j < 4; j++)
#pragma unroll
      for (int e = 0; e < 4; e++) sts32f(y0 + (544 * j + 68 * (e & 1) + 8 * (e >> 1)) * 4, D0[4 * j + e]);
  }
  wg_wait<1>();
  CONV_GO(14)
  wg_wait<1>();
  CONV_ISSUE(15)
  PT(0, wg, 7);
  wg_wait<0>();
  fence_regs<12>(D2); fence_regs<16>(D3a); fence_regs<8>(D3b);
  PT(0, wg, 8);
  {
    const bool odd = g & 1;
#pragma unroll
    for (int e = 0; e < 4; e++) {
      D2[e] += (odd ? D3a[8 + e] : D3a[e]) + (odd ? D3b[4 + e] : D3b[e]);
      D2[4 + e] += odd ? D3a[12 + e] : D3a[4 + e];
    }
    const uint32_t y2 = R + K1_Y2 + (136 * w4 + 8 * g + 2 * t4 + 4 * (g >> 2)) * 4;
#pragma unroll
    for (int gm = 0; gm < 3; gm++)
#pragma unroll
      for (int hf = 0; hf < 2; hf++) sts64f(y2 + (68 * hf + 544 * (2 - gm)) * 4, D2[4 * gm + 2 * hf], D2[4 * gm + 2 * hf + 1]);
  }
  {
    const uint32_t ga2 = prmt(graw, 0, 0x3232);
    const uint32_t yr = R + (8 * t + 8 * (t >> 4) + 4 * ((((t >> 2) & 3) + 1) >> 1)) * 4;
    bar_sync(2 + wg, 128);
    PT(0, wg, 9);
    float4 ya[2][2], yb[2][2];
#pragma unroll
    for (int hf = 0; hf < 2; hf++) {
      ya[hf][0] = lds128f(yr + K1_Y0 + 1088 * 4 * hf); ya[hf][1] = lds128f(yr + K1_Y0 + 1088 * 4 * hf + 16);
      if (hf || t >= 64) { yb[hf][0] = lds128f(yr + K1_Y2 + (1088 * hf - 544) * 4); yb[hf][1] = lds128f(yr + K1_Y2 + (1088 * hf - 544) * 4 + 16); }
      else yb[hf][0] = yb[hf][1] = make_float4(0.f, 0.f, 0.f, 0.f);
    }
    bf16* xo = a.x1T + (d0 + wg) * L_ + 8 * t;
#pragma unroll
    for (int hf = 0; hf < 2; hf++) {
      float y[8] = {ya[hf][0].x + yb[hf][0].x, ya[hf][0].y + yb[hf][0].y, ya[hf][0].z + yb[hf][0].z, ya[hf][0].w + yb[hf][0].w,
                    ya[hf][1].x + yb[hf][1].x, ya[hf][1].y + yb[hf][1].y, ya[hf][1].z + yb[hf][1].z, ya[hf][1].w + yb[hf][1].w};
      if (hf) {
#pragma unroll
        for (int e = 0; e < 8; e++) y[e] += f[e];
      } else { y[6] += f6; y[7] += f7; }
      const uint4 uv = hf ? u1 : u0;
      const uint32_t un[4] = {uv.x, uv.y, uv.z, uv.w};
      uint32_t x1[4];
#pragma unroll
      for (int j = 0; j < 4; j++) x1[j] = hadd2(un[j], hmul2(ga2, hadd2(pack_bf16(y[2 * j], y[2 * j + 1]), hd[hf][j])));
      *(uint4*)(xo + 1024 * hf) = make_uint4(x1[0], x1[1], x1[2], x1[3]);
    }
  }
  PT(0, wg, 10);
}

constexpr int KB_A = 0, KB_A2 = 114688, KB_B = KB_A2 + 3 * 16384, KB_AUG = KB_B + 4 * 14336, KB_BAR = KB_A2 + 7 * 16384, KB_GB = KB_BAR + 640, KB_SMEM = KB_GB + 256;
__host__ __device__ constexpr int kb_wofs(int p) {
  return p == 0 ? 0 : p == 1 ? KB_A2 + 61440 : p == 2 ? 28672 : p == 3 ? KB_A2 + 86528 : p == 4 ? 57344 : p == 5 ? 86016 : p == 6 ? KB_A2 : KB_A2 + 32768;
}

__device__ __forceinline__ float gelu_half(float h) {
  const float u = h * fmaf(h * h, 0.2854192648f, 1.5957691216f);
  float t; asm("tanh.approx.f32 %0, %1;" : "=f"(t) : "f"(u));
  return fmaf(h, t, h);
}
__device__ __forceinline__ float gelu_raw(float a, float k1, float k2) {
  float t; asm("tanh.approx.f32 %0, %1;" : "=f"(t) : "f"(a * fmaf(a * a, k2, k1)));
  return fmaf(a, t, a);
}
__device__ __forceinline__ void quad_stats(uint64_t pa, uint64_t pb, float nb, float n, float inv_tot, float& mean, float& var) {
  const float sa = __uint_as_float((uint32_t)pa), sb = __uint_as_float((uint32_t)pb);
  float s = sa + sb;
  s += __shfl_xor_sync(~0u, s, 1); s += __shfl_xor_sync(~0u, s, 2);
  mean = s * inv_tot;
  const float da = fmaf(sa, 1.0f / n, -mean), db = fmaf(sb, 1.0f / n, -mean);
  float q = __uint_as_float((uint32_t)(pa >> 32)) + __uint_as_float((uint32_t)(pb >> 32)) + fmaf(n * da, da, nb * db * db);
  q += __shfl_xor_sync(~0u, q, 1); q += __shfl_xor_sync(~0u, q, 2);
  var = q * inv_tot;
}
__device__ __forceinline__ void gather4(const uint2* base, int hi_ofs, uint32_t tag, uint64_t* p) {
  for (uint32_t it = 0;; it++) {
#pragma unroll
    for (int i = 0; i < 4; i++) asm volatile("ld.relaxed.gpu.global.b64 %0, [%1];" : "=l"(p[i]) : "l"(base + (i >> 1) * hi_ofs + 8 * (i & 1)) : "memory");
    if (!((((uint32_t)(p[0] >> 32) ^ tag) | ((uint32_t)(p[1] >> 32) ^ tag) | ((uint32_t)(p[2] >> 32) ^ tag) | ((uint32_t)(p[3] >> 32) ^ tag)) & 0xFFu)) break;
    if (it > (1u << 22)) __trap();
  }
  __syncwarp();
}

#define NPRE 5
#define WSTART relA
#define JSH 4
constexpr uint64_t kb_wtab() { uint64_t v = 0; for (int p = 0; p < 8; p++) v |= (uint64_t)(kb_wofs(p) / 1024) << (8 * p); return v; }
constexpr uint64_t KB_WOFS = kb_wtab();
#define NZ1 3
struct KBArgs { const bf16* b_sp; const unsigned int* epoch; const uint8_t *wimg, *waug; uint2 *xstat, *zstat; unsigned int* zcnt; uint8_t *z2img, *pimg; const bf16* w_out; uint8_t* woimg; unsigned int* pcnt; const uint32_t* mod; unsigned int* epoch_w; };

__global__ void __cluster_dims__(2, 1, 1) __launch_bounds__(384, 1)
kb_gemm12(const __grid_constant__ CUtensorMap tm_xs, const __grid_constant__ CUtensorMap tm_wsp, const __grid_constant__ CUtensorMap tm_x1,
          const __grid_constant__ CUtensorMap tm_out, const KBArgs a) {
  extern __shared__ __align__(1024) uint8_t smem_raw[];
  const uint32_t sm = smem_u32(smem_raw);
  const int tid = threadIdx.x, warp = __shfl_sync(~0u, tid >> 5, 0), lane = tid & 31;
  const int cl = blockIdx.x >> 1, j = (cl >> JSH) & 3, T = (cl & ((1 << JSH) - 1)) | ((cl >> (JSH + 2)) << JSH), kap = blockIdx.x & 1, ph = 2 * j + kap;
  const int wg = warp >> 2, w4 = warp & 3, g = lane >> 2, t4 = lane & 3;
  const uint32_t fullA = sm + KB_BAR, fullB = fullA + 56, fullA2 = fullB + 112, fullB2 = fullA2 + 56, barG = fullB2 + 32, xfull = barG + 8, rdy = xfull + 8;
  const uint32_t emptyB = rdy + 64, emptyA2 = emptyB + 56, emptyB2 = emptyA2 + 56, bar1 = emptyB2 + 32, xfree = bar1 + 8, relA = xfree + 8, xdone = relA + 8, wrdy = xdone + 8, g0done = wrdy + 8, zst = g0done + 8;
  const uint32_t sb = sm + KB_B;
  const int k0 = 2 * j;
  PT(1, wg, 0);
  const uint32_t tagraw = ldg32_nc(a.epoch);
  if (lane == 0) {
#pragma unroll 1
    for (int i = warp; i < 67; i += 12) mbar_init(fullA + 8 * i, i == 63 || i == 66 ? 8 : i < 42 || i > 63 ? 1 : 2);
    asm volatile("fence.mbarrier_init.release.cluster;" ::: "memory");
  }
  __syncthreads();
  asm volatile("barrier.cluster.arrive.relaxed.aligned;" ::: "memory");
  if (tid == 256) {
    tmap_prefetch(&tm_xs); tmap_prefetch(&tm_wsp);
#pragma unroll 1
    for (int i = 0, kb = k0; i < 4; i++) {
      mbar_expect_tx(fullB + 8 * i, 14336);
      bulk_load(sb + i * 14336, a.wimg + ((8 + ph) * 7 + kb) * 14336, 14336, fullB + 8 * i);
      if (++kb == 7) kb = 0;
    }
    mbar_expect_tx(xfull, 28672);
  }
  __syncwarp();
  const uint32_t tag = (tagraw + 1u) & 0xFFu;
  if (wg == 2) {
    asm volatile("barrier.cluster.wait.aligned;" ::: "memory");
    if (warp == 8) {
      if (lane == 0) {
        pdl_wait();
        PT(1, 2, 1);
#pragma unroll 1
        for (int i = 0; i < 7; i++) {
          const int sl = i < 2 ? i ^ kap : i;
          const int kb = k0 + sl >= 7 ? k0 + sl - 7 : k0 + sl;
          mbar_expect_tx(fullA + 8 * sl, 16384);
          tma_load_2d_mc(sm + KB_A + sl * 16384 + kap * 8192, &tm_xs, T * 128 + kap * 64, kb * 64, fullA + 8 * sl, 3);
        }
        mbar_expect_tx(barG, 7168);
        bulk_load(sm + KB_AUG, a.waug + (8 + ph) * 3584, 3584, barG);
        bulk_load(sm + KB_AUG + 3584, a.waug + ph * 3584, 3584, barG);
#pragma unroll 1
        for (int i = 4; i < 14; i++) {
          const int kb = (k0 + i) % 7;
          if (i == 11) {
#pragma unroll 1
            for (int q = 0; q < 3; q++) {
              mbar_expect_tx(fullA2 + 8 * q, 16384);
              tma_load_2d(sm + KB_A2 + q * 16384, &tm_wsp, kap * 1024 + q * 64, T * 128, fullA2 + 8 * q);
            }
          }
          mbar_wait(emptyB + 8 * (i & 3), ((i >> 2) & 1) ^ 1);
          mbar_expect_tx(fullB + 8 * i, 14336);
          bulk_load(sb + (i & 3) * 14336, a.wimg + ((i >= 7 ? ph : 8 + ph) * 7 + kb) * 14336, 14336, fullB + 8 * i);
        }
        mbar_wait(relA, 0);
        PT(2, 2, 1);
        const uint8_t* zsrc = a.z2img + ((size_t)(kap * 16) * 4 + j) * 28672;
        int na = 3, sa = 3;
#pragma unroll 1
        for (int kb = 0; kb < 16; kb++) {
          const int s = kb & 3;
          if (!(kb & 1)) mbar_wait(rdy + 4 * kb, 0);
          if (kb == 0) PT(2, 2, 2);
          if (kb == 1) mbar_wait(bar1, 0);
          if (kb >= 4) mbar_wait(emptyB2 + 8 * s, ((kb >> 2) & 1) ^ 1);
          mbar_expect_tx(fullB2 + 8 * s, 28672);
          bulk_load(sm + s * 28672, zsrc + (size_t)kb * 4 * 28672 + kap * 14336, 14336, fullB2 + 8 * s);
          bulk_load(sm + s * 28672 + 14336, zsrc + (size_t)kb * 4 * 28672 + (kap ^ 1) * 14336, 14336, fullB2 + 8 * s);
#pragma unroll 1
          while (na < 16 && na < (kb < 3 ? kb + 2 : kb < 4 ? NPRE : kb + 4)) {
            if (na >= 7) mbar_wait(emptyA2 + 8 * sa, na >= 14);
            mbar_expect_tx(fullA2 + 8 * sa, 16384);
            tma_load_2d(sm + KB_A2 + sa * 16384, &tm_wsp, kap * 1024 + na * 64, T * 128, fullA2 + 8 * sa);
            na++; if (++sa == 7) sa = 0;
          }
        }
        mbar_wait(wrdy, 0);
#pragma unroll 1
        for (int p = 0; p < 8; p++) {
          if (p < 7) mbar_wait(emptyB2 + 8 * ((0x3321100 >> (4 * p)) & 3), 1); else mbar_wait(xdone, 0);
          mbar_expect_tx(fullB + 8 * p, 25088);
          bulk_load(sm + ((KB_WOFS >> (8 * p)) & 255) * 1024 + (p == 3 ? 512 : 0), a.woimg + (j * 8 + p) * 25088, 25088, fullB + 8 * p);
        }
        mbar_wait(g0done, 0);
        mbar_expect_tx(fullB + 64, 14336);
        tma_load_2d(sm, &tm_x1, (2 * T + kap) * 64, j * 112, fullB + 64);
      }
    } else {
      const int st = tid - 288;
      if (blockIdx.x < 112) {
        const int f = blockIdx.x * 8 + (st & 7);
#pragma unroll 1
        for (int dc = st >> 3; dc < 56; dc += 12)
          *(uint4*)(a.woimg + ((dc / 14) * 8 + f / 112) * 25088 + (dc % 14) * 1792 + ((f % 112) >> 3) * 128 + (f & 7) * 16) = ldg128_nc(a.w_out + f * D_ + dc * 8);
      }
      bar_sync(3, 96);
      if (st == 0) asm volatile("red.release.gpu.global.add.u32 [%0], 1;" ::"l"(a.pcnt + 32 * 32) : "memory");
      if (tid == 352) {
        mbar_wait(zst, 0);
        asm volatile("red.release.gpu.global.add.u32 [%0], 1;" ::"l"(a.zcnt + (T * 4 + j) * 32) : "memory");
        PTX2(9);
      }
      if (warp == 10) {
        const unsigned int* cnt = a.zcnt + ((kap * 8 + (lane & 7)) * 4 + j) * 32;
        const uint32_t target = (tagraw + 1u) * 2u;
        if (ld_rlx32(cnt) == target) __trap();
        mbar_wait(WSTART, 0);
        uint32_t seen = 0;
        for (uint32_t it = 0; seen != 0xFFu; it++) {
          const unsigned int v = ld_rlx32(cnt);
          const uint32_t now = __ballot_sync(~0u, (int)(v - target) >= 0) & 0xFFu;
          if (it > (1u << 22)) __trap();
          if (now == 0xFFu) {
            asm volatile("fence.proxy.async.global;" ::: "memory");
            if (lane < 8 && (((now & ~seen) >> lane) & 1)) mbar_arrive(rdy + 8 * lane);
            seen = now;
          }
        }
        for (uint32_t it = 0; (int)(ld_rlx32(a.pcnt + 32 * 32) - (tagraw + 1u) * 128u) < 0; it++) if (it > (1u << 22)) __trap();
        ld_rlx32(a.pcnt + (2 * T + kap) * 32);
        pdl_wait();
        if (lane < 28) { const uint4 m = ldg128_cg(a.mod + 5 * D_ + j * 112 + 4 * lane); sts64(sm + KB_GB + lane * 8, prmt(m.x, m.y, 0x7632), prmt(m.z, m.w, 0x7632)); }
        if (lane == 0) { tmap_prefetch(&tm_x1); tmap_prefetch(&tm_out); }
        asm volatile("fence.acq_rel.gpu;" ::: "memory");
        asm volatile("fence.proxy.async.global;" ::: "memory");
        __syncwarp();
        if (lane == 0) mbar_arrive(wrdy);
      }
    }
    return;
  }

  const int r0 = wg * 64 + w4 * 16 + g;
  const uint32_t b0 = ldg16_nc(a.b_sp + T * 128 + r0) * 0x10001u, b1 = ldg16_nc(a.b_sp + T * 128 + r0 + 8) * 0x10001u;
  uint32_t z1[28];
  {
    const uint64_t da0 = mkdesc(sm + KB_A + wg * 8192, desc_hi(8192, 1024, 1)), db0 = mkdesc(sb, desc_hi(128, 1024, 0));
    const uint64_t daug = mkdesc(sm + KB_AUG, desc_hi(128, 256, 0));
    float a2[56], a1[56];
#define KB_MMA(i, kb, ACC)                                                                                                \
      mbar_wait(fullB + 8 * (i), 0);                                                                                      \
      wg_fence();                                                                                                         \
      _Pragma("unroll") for (int k = 0; k < 4; k++)                                                                       \
        wgmma_ss_n112<1, 1>(ACC, da0 + (kb) * 1024 + k * 128, db0 + ((i) & 3) * 896 + k * 16, ((kb) | k) != 0);                \
      wg_commit();
    mbar_wait(fullA + 8 * kap, 0);
    PT(1, wg, 1);
    if (ph < 7) {
      float cs[4] = {0.f, 0.f, 0.f, 0.f}, ql[4] = {0.f, 0.f, 0.f, 0.f}, qh[4] = {0.f, 0.f, 0.f, 0.f};
      const uint32_t ad = sm + KB_A + kap * 16384 + wg * 8192 + ((lane & 7) + (lane >> 4) * 8) * 128 + (((w4 * 2 + ((lane >> 3) & 1)) ^ (lane & 7)) << 4);
      uint32_t f[4][4];
#pragma unroll
      for (int ks = 0; ks < 4; ks++) ldsm4t(ad + ks * 2048, f[ks][0], f[ks][1], f[ks][2], f[ks][3]);
#pragma unroll
      for (int ks = 0; ks < 4; ks++) {
        mma16816(cs, f[ks][0], f[ks][1], f[ks][2], f[ks][3], 0x3F803F80u, 0x3F803F80u);
        mma16816(ql, f[ks][0], f[ks][1], f[ks][2], f[ks][3], f[ks][0], f[ks][2]);
        mma16816(qh, f[ks][0], f[ks][1], f[ks][2], f[ks][3], f[ks][1], f[ks][3]);
      }
      if (t4 == (g >> 1)) {
        const float q0 = fmaxf(fmaf(-cs[0], cs[0] * (1.0f / 64.f), (g & 1) ? ql[1] : ql[0]), 0.f), q1 = fmaxf(fmaf(-cs[2], cs[2] * (1.0f / 64.f), (g & 1) ? qh[3] : qh[2]), 0.f);
        uint2* o = a.xstat + (T * 8 + ph) * 128 + r0;
        st_rlx64x(o, __float_as_uint(cs[0]), (__float_as_uint(q0) & ~0xFFu) | tag);
        st_rlx64x(o + 8, __float_as_uint(cs[2]), (__float_as_uint(q1) & ~0xFFu) | tag);
      }
      __syncwarp();
    }
    PT(1, wg, 9);
#define KB_Z2(kb) { mbar_wait(fullA + 8 * (kb), 0); KB_MMA(kb, kb, a2) if ((kb) >= 1) { wg_wait<1>(); if ((tid & 127) == 0) mbar_arrive(emptyB + 8 * (((kb) - 1) & 3)); } }
#pragma unroll 1
    for (int kb = 0; kb < 3; kb++) KB_Z2(kb)
    uint64_t p[4];
    const uint2* xs = a.xstat + (T * 8 + t4) * 128 + r0;
#pragma unroll
    for (int i = 0; i < 4; i++) asm volatile("ld.relaxed.gpu.global.b64 %0, [%1];" : "=l"(p[i]) : "l"(xs + (i >> 1) * (t4 == 3 ? 0 : 512) + 8 * (i & 1)) : "memory");
#pragma unroll 1
    for (int kb = 3; kb < 5; kb++) KB_Z2(kb)
    PT(1, wg, 10);
    float m0, m1, v0, v1;
    if (__any_sync(~0u, (((uint32_t)(p[0] >> 32) ^ tag) | ((uint32_t)(p[1] >> 32) ^ tag) | ((uint32_t)(p[2] >> 32) ^ tag) | ((uint32_t)(p[3] >> 32) ^ tag)) & 0xFFu))
      gather4(xs, t4 == 3 ? 0 : 512, tag, p);
    if (t4 == 3) p[2] = p[3] = 0ull;
    quad_stats(p[0], p[2], t4 == 3 ? 0.f : 64.f, 64.f, 1.0f / D_, m0, v0);
    quad_stats(p[1], p[3], t4 == 3 ? 0.f : 64.f, 64.f, 1.0f / D_, m1, v1);
    v0 = ln_den(v0); v1 = ln_den(v1);
    const uint32_t g0 = t4 == 0 ? pack_bf16(-m0, -m0) : t4 == 1 ? pack_bf16(v0, v0) : 0u;
    const uint32_t g1 = t4 == 0 ? pack_bf16(-m1, -m1) : t4 == 1 ? pack_bf16(v1, v1) : 0u;
    KB_Z2(5)
    mbar_wait(fullA + 8 * 6, 0);
    mbar_wait(barG, 0);
    KB_MMA(6, 6, a2)
    wg_fence();
    wgmma_rs_n112_tb(a2, g0, g1, 0u, 0u, daug, 1);
    wg_commit();
    wg_wait<2>();
    if ((tid & 127) == 0) mbar_arrive(emptyB + 8 * 1);
    PT(1, wg, 3);
    wg_wait<0>();
    fence_regs<56>(a2);
    if ((tid & 127) == 0) mbar_arrive(emptyB + 8 * 2);
    PT(1, wg, 2);
    const float rx = 0.5f * rcp_fast(v0), ry = 0.5f * rcp_fast(v1);
    {
      const float k1x = 1.5957691216f * rx, k2x = 0.2854192648f * rx * rx * rx, k1y = 1.5957691216f * ry, k2y = 0.2854192648f * ry * ry * ry;
      float s0 = 0.f, q0 = 0.f, s1 = 0.f, q1 = 0.f;
#pragma unroll
      for (int i = 0; i < 14; i++) {
        const float a = gelu_raw(a2[4 * i], k1x, k2x), b = gelu_raw(a2[4 * i + 1], k1x, k2x), c = gelu_raw(a2[4 * i + 2], k1y, k2y), d = gelu_raw(a2[4 * i + 3], k1y, k2y);
        a2[4 * i] = a; a2[4 * i + 1] = b; a2[4 * i + 2] = c; a2[4 * i + 3] = d;
        s0 += a + b; q0 = fmaf(a, a, fmaf(b, b, q0));
        s1 += c + d; q1 = fmaf(c, c, fmaf(d, d, q1));
      }
#pragma unroll
      for (int o = 1; o < 4; o <<= 1) { s0 += __shfl_xor_sync(~0u, s0, o); q0 += __shfl_xor_sync(~0u, q0, o); s1 += __shfl_xor_sync(~0u, s1, o); q1 += __shfl_xor_sync(~0u, q1, o); }
      const float ss = t4 ? s1 : s0, qq = t4 ? q1 : q0, rr = t4 ? ry : rx;
      const float m2 = fmaxf(fmaf(-ss, ss * (1.0f / 112.f), qq), 0.f) * rr * rr;
      if (t4 < 2) st_rlx64x(a.zstat + (T * 8 + ph) * 128 + r0 + 8 * t4, __float_as_uint(ss * rr), (__float_as_uint(m2) & ~0xFFu) | tag);
    }
    PT(1, wg, 4);
#pragma unroll 1
    for (int kb = 0; kb < NZ1; kb++) { KB_MMA(7 + kb, kb, a1) }
    gather4(a.zstat + (T * 8 + t4) * 128 + r0, 512, tag, p);
    PT(1, wg, 7);
    wg_wait<0>();
    if ((tid & 127) == 0) { mbar_arrive(emptyB + 24); mbar_arrive(emptyB); mbar_arrive(emptyB + 8); mbar_arrive(relA); }
    quad_stats(p[0], p[2], 112.f, 112.f, 1.0f / FH_, m0, v0);
    quad_stats(p[1], p[3], 112.f, 112.f, 1.0f / FH_, m1, v1);
    {
      const float j0 = ln_rden(v0), j1 = ln_rden(v1);
      const float o0 = -bf_round(m0) * j0, o1 = -bf_round(m1) * j1, i0 = j0 * rx, i1 = j1 * ry;
      PT(1, wg, 11);
      uint8_t* dst = a.z2img + ((2 * T + wg) * 4 + j) * 28672 + kap * 14336 + (2 * w4) * 128 + lane * 4;
#pragma unroll
      for (int i = 0; i < 14; i++) {
        *(uint32_t*)(dst + i * 1024) = pack_bf16(fmaf(a2[4 * i], i0, o0), fmaf(a2[4 * i + 1], i0, o0));
        *(uint32_t*)(dst + i * 1024 + 128) = pack_bf16(fmaf(a2[4 * i + 2], i1, o1), fmaf(a2[4 * i + 3], i1, o1));
      }
    }
    PT(1, wg, 12);
    __syncwarp();
    if (lane == 0) mbar_arrive(zst);
    __syncwarp();
    PT(1, wg, 8);
#pragma unroll 1
    for (int kb = NZ1; kb < 7; kb++) { KB_MMA(7 + kb, kb, a1) }
    wg_fence();
    wgmma_rs_n112_tb(a1, g0, g1, 0u, 0u, daug + 224, 1);
    wg_commit();
    wg_wait<0>();
    fence_regs<56>(a1);
    if ((tid & 127) == 0) mbar_arrive(bar1);
    PT(1, wg, 5);
#pragma unroll
    for (int i = 0; i < 28; i++) { const float rr = (i & 1) ? ry : rx; z1[i] = pack_bf16(gelu_half(a1[2 * i] * rr), gelu_half(a1[2 * i + 1] * rr)); }
    PT(1, wg, 6);
  }
  float acc[112];
  const uint64_t dA = mkdesc(sm + KB_A2 + wg * 8192, desc_hi(16, 1024, 1)), dB = mkdesc(sm, desc_hi(128, 1024, 0));
  asm volatile("barrier.cluster.wait.aligned;" ::: "memory");
  int sa = 0, pa = 0;
#pragma unroll 1
  for (int kb = 0; kb < 16; kb++) {
    mbar_wait(fullA2 + 8 * sa, pa);
    mbar_wait(fullB2 + 8 * (kb & 3), (kb >> 2) & 1);
    if (kb == 0) PT(2, wg, 1);
    if (kb == 8) PT(2, wg, 2);
    wg_fence();
#pragma unroll
    for (int k = 0; k < 4; k++) wgmma_ss_n224<0, 1>(acc, dA + sa * 1024 + k * 2, dB + (kb & 3) * 1792 + k * 16, (kb | k) != 0);
    wg_commit();
    if (kb > 0) {
      wg_wait<1>();
      if ((tid & 127) == 0) {
        mbar_arrive(emptyB2 + 8 * ((kb - 1) & 3));
        if (kb <= 9) mbar_arrive(emptyA2 + 8 * (sa == 0 ? 6 : sa - 1));
        if (kb == 11) mbar_arrive_remote(mapa(xfree, kap ^ 1));
      }
    }
    if (++sa == 7) { sa = 0; pa ^= 1; }
  }
  wg_wait<0>();
  fence_regs<112>(acc);
  if ((tid & 127) == 0) mbar_arrive(emptyB2 + 24);
  PT(2, wg, 3);
  const uint32_t xb = sm + KB_A2 + 2 * 16384 + tid * 16;
  mbar_wait(xfree, 0);
  {
    const uint32_t dst = mapa(xb, kap ^ 1), rb = mapa(xfull, kap ^ 1);
    const float* snd = acc + 56;
#pragma unroll
    for (int q = 0; q < 7; q++)
      asm volatile("st.async.shared::cluster.mbarrier::complete_tx::bytes.v4.b32 [%0], {%1,%2,%3,%4}, [%5];" ::"r"(dst + q * 4096), "r"(pack_bf16(snd[8 * q], snd[8 * q + 1])),
                   "r"(pack_bf16(snd[8 * q + 2], snd[8 * q + 3])), "r"(pack_bf16(snd[8 * q + 4], snd[8 * q + 5])), "r"(pack_bf16(snd[8 * q + 6], snd[8 * q + 7])), "r"(rb) : "memory");
  }
  PT(2, wg, 4);
  mbar_wait(xfull, 0);
  PT(2, wg, 5);
  uint4* dst = (uint4*)(a.pimg + ((2 * T + wg) * 8 + ph) * 14336) + (tid & 127);
#pragma unroll
  for (int q = 0; q < 7; q++) {
    const uint4 v = lds128(xb + q * 4096);
    const uint32_t w[4] = {v.x, v.y, v.z, v.w};
    uint32_t o[4];
#pragma unroll
    for (int i = 0; i < 4; i++)
      o[i] = hmul2(z1[4 * q + i], hadd2(pack_bf16(acc[8 * q + 2 * i] + bf_lo(w[i]), acc[8 * q + 2 * i + 1] + bf_hi(w[i])), (i & 1) ? b1 : b0));
    dst[q * 128] = make_uint4(o[0], o[1], o[2], o[3]);
  }
  PT(2, wg, 6);
  __syncwarp();
  if (lane == 0) { mbar_arrive(xdone); asm volatile("red.release.gpu.global.add.u32 [%0], 1;" ::"l"(a.pcnt + (2 * T + wg) * 32) : "memory"); }
  __syncwarp();
  PT(2, wg, 7);
  {
    const unsigned int* cnt = a.pcnt + (2 * T + kap) * 32;
#pragma unroll 1
    for (int p = 0; p < 3; p++) mbar_wait(fullB + 16 * p + 8 * wg, 1);
    for (uint32_t it = 0; (int)(ld_rlx32(cnt) - (tagraw + 1u) * 32u) < 0; it++) if (it > (1u << 22)) __trap();
    __syncwarp();
    PT(3, wg, 4);
    float o3[56];
    const uint64_t dW = mkdesc(sm, desc_hi(128, 1792, 0));
    const uint4* asrc = (const uint4*)(a.pimg + ((2 * T + kap) * 8 + wg) * 14336) + (tid & 127);
    uint4 af[3][7];
#pragma unroll
    for (int p = 0; p < 3; p++)
#pragma unroll
      for (int k = 0; k < 7; k++) af[p][k] = ld_rlx2x64(asrc + p * 1792 + k * 128);
#pragma unroll
    for (int p = 0; p < 4; p++) {
      if (p == 3) mbar_wait(fullB + 48 + 8 * wg, 1);
      const uint64_t dp = dW + (wg ? kb_wofs(2 * p + 1) : kb_wofs(2 * p)) / 16;
      wg_fence();
#pragma unroll
      for (int k = 0; k < 7; k++) wgmma_rs_n112_tb(o3, af[p % 3][k].x, af[p % 3][k].y, af[p % 3][k].z, af[p % 3][k].w, dp + k * 16, (p | k) != 0);
      wg_commit();
      if (p == 0) PT(3, wg, 1);
      if (p == 1) {
        wg_wait<1>();
#pragma unroll
        for (int k = 0; k < 7; k++) af[0][k] = ld_rlx2x64(asrc + 3 * 1792 + k * 128);
      }
      if (p == 2 && wg == 0) { bar_sync(1, 128); if (tid == 0) mbar_arrive(g0done); }
    }
    wg_wait<0>();
    fence_regs<56>(o3);
    const uint32_t rb = sm + kb_wofs(1) + (tid & 127) * 16;
    if (wg == 1) {
      bar_sync(2, 128);
#pragma unroll
      for (int q = 0; q < 12; q++) sts128(rb + q * 2048, make_uint4(__float_as_uint(o3[4 * q]), __float_as_uint(o3[4 * q + 1]), __float_as_uint(o3[4 * q + 2]), __float_as_uint(o3[4 * q + 3])));
#pragma unroll
      for (int q = 12; q < 14; q++) sts128(rb + 25088 + (q - 12) * 2048, make_uint4(__float_as_uint(o3[4 * q]), __float_as_uint(o3[4 * q + 1]), __float_as_uint(o3[4 * q + 2]), __float_as_uint(o3[4 * q + 3])));
      bar_arrive(4, 256);
      if (blockIdx.x == 0 && tid == 128) *a.epoch_w = tagraw + 1u;
      return;
    }
    bar_sync(4, 256);
#pragma unroll
    for (int q = 0; q < 14; q++) {
      const float4 v = lds128f(rb + (q < 12 ? q * 2048 : 25088 + (q - 12) * 2048));
      o3[4 * q] += v.x; o3[4 * q + 1] += v.y; o3[4 * q + 2] += v.z; o3[4 * q + 3] += v.w;
    }
    PT(3, 0, 2);
    mbar_wait(fullB + 64, 1);
    const int mj = lane >> 3;
#pragma unroll
    for (int jj = 0; jj < 7; jj++) {
      uint32_t x[4], o[4];
      const int dr = (2 * jj + (mj >> 1)) * 8 + (lane & 7), sc = 2 * warp + (mj & 1);
      ldsm4t(sm + dr * 128 + ((sc ^ (dr & 7)) << 4), x[0], x[1], x[2], x[3]);
      const uint32_t ga0 = lds32(sm + KB_GB + (8 * jj + t4) * 4), ga1 = lds32(sm + KB_GB + (8 * jj + 4 + t4) * 4);
      o[0] = hadd2(x[0], hmul2(ga0, pack_bf16(o3[8 * jj], o3[8 * jj + 1])));
      o[1] = hadd2(x[1], hmul2(ga0, pack_bf16(o3[8 * jj + 2], o3[8 * jj + 3])));
      o[2] = hadd2(x[2], hmul2(ga1, pack_bf16(o3[8 * jj + 4], o3[8 * jj + 5])));
      o[3] = hadd2(x[3], hmul2(ga1, pack_bf16(o3[8 * jj + 6], o3[8 * jj + 7])));
      stsm4(sm + 14336 + (16 * warp + (mj & 1) * 8 + (lane & 7)) * 224 + (2 * jj + (mj >> 1)) * 16, o[0], o[1], o[2], o[3]);
    }
    fence_async_smem();
    bar_sync(1, 128);
    if (tid == 0) { tma_store_2d(&tm_out, sm + 14336, j * 112, (2 * T + kap) * 64); bulk_commit(); bulk_wait_read(); }
    PT(3, 0, 3);
  }
}

typedef CUresult (*PFN_tmEncode)(CUtensorMap*, CUtensorMapDataType, cuuint32_t, void*, const cuuint64_t*, const cuuint64_t*, const cuuint32_t*, const cuuint32_t*,
                                 CUtensorMapInterleave, CUtensorMapSwizzle, CUtensorMapL2promotion, CUtensorMapFloatOOBfill);
static CUtensorMap make_map(PFN_tmEncode enc, const void* base, uint64_t inner, uint64_t outer, uint32_t bi, uint32_t bo, CUtensorMapSwizzle sw) {
  CUtensorMap m; cuuint64_t gd[2] = {inner, outer}; cuuint64_t gs[1] = {inner * 2}; cuuint32_t bd[2] = {bi, bo}; cuuint32_t es[2] = {1, 1};
  enc(&m, CU_TENSOR_MAP_DATA_TYPE_BFLOAT16, 2, (void*)base, gd, gs, bd, es, CU_TENSOR_MAP_INTERLEAVE_NONE, sw, CU_TENSOR_MAP_L2_PROMOTION_L2_256B, CU_TENSOR_MAP_FLOAT_OOB_FILL_NONE);
  return m;
}
template <typename... KA, typename... A>
static void launch(void (*k)(KA...), int grid, int block, int smem, bool pdl, A... args) {
  cudaLaunchConfig_t cfg = {};
  cfg.gridDim = dim3(grid); cfg.blockDim = dim3(block); cfg.dynamicSmemBytes = smem; cfg.stream = cudaStreamPerThread;
  cudaLaunchAttribute at[1];
  at[0].id = cudaLaunchAttributeProgrammaticStreamSerialization; at[0].val.programmaticStreamSerializationAllowed = 1;
  cfg.attrs = at; cfg.numAttrs = pdl ? 1 : 0;
  cudaLaunchKernelEx(&cfg, k, args...);
}

extern "C" void kernel_launch(void* const* d_in, const int* in_sizes, int n_in, void* d_out, int out_size) {
  static PFN_tmEncode enc = nullptr;
  static void *p_x1T, *p_epoch, *p_kmap, *p_stat1, *p_mod, *p_wimg, *p_waug, *p_woimg, *p_uT, *p_xstat, *p_zstat, *p_zcnt, *p_z2img, *p_pimg, *p_pcnt;
  if (!enc) {
    void* p = nullptr; cudaDriverEntryPointQueryResult q;
    cudaGetDriverEntryPoint("cuTensorMapEncodeTiled", &p, cudaEnableDefault, &q);
    enc = (PFN_tmEncode)p;
    cudaGetSymbolAddress(&p_x1T, g_x1T); cudaGetSymbolAddress(&p_epoch, g_epoch); cudaGetSymbolAddress(&p_kmap, g_kmap); cudaGetSymbolAddress(&p_stat1, g_stat1);
    cudaGetSymbolAddress(&p_mod, g_mod); cudaGetSymbolAddress(&p_wimg, g_wimg); cudaGetSymbolAddress(&p_waug, g_waug); cudaGetSymbolAddress(&p_woimg, g_woimg); cudaGetSymbolAddress(&p_uT, g_uT);
    cudaGetSymbolAddress(&p_xstat, g_xstat); cudaGetSymbolAddress(&p_zstat, g_zstat); cudaGetSymbolAddress(&p_zcnt, g_zcnt); cudaGetSymbolAddress(&p_z2img, g_z2img); cudaGetSymbolAddress(&p_pimg, g_pimg); cudaGetSymbolAddress(&p_pcnt, g_pcnt);
    cudaFuncSetAttribute(k1_conv, cudaFuncAttributeMaxDynamicSharedMemorySize, K1_SMEM);
    cudaFuncSetAttribute(kb_gemm12, cudaFuncAttributeMaxDynamicSharedMemorySize, KB_SMEM);
  }
  K1Args a;
  a.u = (const bf16*)d_in[0]; a.Are = (const bf16*)d_in[1]; a.Aim = (const bf16*)d_in[2]; a.Bre = (const bf16*)d_in[3]; a.Bim = (const bf16*)d_in[4];
  a.Cre = (const bf16*)d_in[5]; a.Cim = (const bf16*)d_in[6]; a.logdt = (const bf16*)d_in[7]; a.dskip = (const bf16*)d_in[8];
  a.c = (const bf16*)d_in[14]; a.w_mod = (const bf16*)d_in[15]; a.w_in = (const bf16*)d_in[10]; a.w_sp = (const bf16*)d_in[11];
  a.epoch = (const unsigned int*)p_epoch; a.kmap = (const uint32_t*)p_kmap; a.mod = (uint32_t*)p_mod; a.uT = (uint2*)p_uT; a.stat1 = (uint2*)p_stat1;
  a.x1T = (bf16*)p_x1T; a.wimg = (uint8_t*)p_wimg; a.waug = (uint8_t*)p_waug;
  const CUtensorMap tm_x1a = make_map(enc, p_x1T, L_, D_, 64, 64, CU_TENSOR_MAP_SWIZZLE_128B);
  const CUtensorMap tm_wsp = make_map(enc, d_in[11], L_, L_, 64, 128, CU_TENSOR_MAP_SWIZZLE_128B);
  const CUtensorMap tm_x1 = make_map(enc, p_x1T, L_, D_, 64, 112, CU_TENSOR_MAP_SWIZZLE_128B);
  const CUtensorMap tm_out = make_map(enc, d_out, D_, L_, 112, 64, CU_TENSOR_MAP_SWIZZLE_NONE);
  const CUtensorMap tm_wmod1 = make_map(enc, d_in[15], 6 * D_, D_, 64, 224, CU_TENSOR_MAP_SWIZZLE_128B);
  const CUtensorMap tm_win = make_map(enc, d_in[10], F_, D_, 64, 224, CU_TENSOR_MAP_SWIZZLE_128B);
  launch(k1_conv, 128, 512, K1_SMEM, false, a, tm_wmod1, tm_win);
  KBArgs b;
  b.b_sp = (const bf16*)d_in[12]; b.epoch = a.epoch; b.wimg = a.wimg; b.waug = a.waug; b.xstat = (uint2*)p_xstat; b.zstat = (uint2*)p_zstat;
  b.zcnt = (unsigned int*)p_zcnt; b.z2img = (uint8_t*)p_z2img; b.pimg = (uint8_t*)p_pimg;
  b.w_out = (const bf16*)d_in[13]; b.woimg = (uint8_t*)p_woimg; b.pcnt = (unsigned int*)p_pcnt; b.mod = a.mod; b.epoch_w = (unsigned int*)p_epoch;
  launch(kb_gemm12, 128, 384, KB_SMEM, true, tm_x1a, tm_wsp, tm_x1, tm_out, b);
}
```

```cpp
#include <cuda_runtime.h>
#include <cuda.h>
#include <cuda_bf16.h>
#include <stdint.h>

typedef __nv_bfloat16 bf16;
typedef __nv_bfloat162 bf162;

constexpr int L_ = 2048, D_ = 448, NM_ = 256, F_ = 1792, FH_ = 896;

__device__ __align__(16) uint2 g_xstat[L_ * 8];
__device__ __align__(16) uint2 g_stat1[L_];
__device__ __align__(128) uint2 g_uT[112 * L_];
__device__ __align__(16) uint32_t g_mod[6 * D_];
__device__ __align__(1024) bf16 g_x1T[D_ * L_];
__device__ __align__(1024) uint8_t g_wimg[16 * 7 * 14336];
__device__ __align__(1024) uint8_t g_waug[16 * 3584];
__device__ __align__(1024) uint8_t g_woimg[4 * 8 * 25088];
__device__ __align__(16) uint2 g_zstat[L_ * 8];
__device__ unsigned int g_zcnt[64 * 32];
__device__ unsigned int g_pcnt[33 * 32];
__device__ __align__(1024) uint8_t g_z2img[32 * 4 * 28672];
__device__ __align__(1024) uint8_t g_pimg[32 * 8 * 14336];
__device__ unsigned int g_epoch;

__device__ __forceinline__ uint32_t smem_u32(const void* p) { return (uint32_t)__cvta_generic_to_shared(p); }
__device__ __forceinline__ void mbar_init(uint32_t bar, uint32_t cnt) { asm volatile("mbarrier.init.shared::cta.b64 [%0], %1;" ::"r"(bar), "r"(cnt) : "memory"); }
__device__ __forceinline__ void mbar_expect_tx(uint32_t bar, uint32_t bytes) { asm volatile("mbarrier.arrive.expect_tx.shared::cta.b64 _, [%0], %1;" ::"r"(bar), "r"(bytes) : "memory"); }
__device__ __forceinline__ void mbar_arrive(uint32_t bar) { asm volatile("mbarrier.arrive.shared::cta.b64 _, [%0];" ::"r"(bar) : "memory"); }
__device__ __forceinline__ uint32_t mapa(uint32_t addr, uint32_t cta) { uint32_t r; asm volatile("mapa.shared::cluster.u32 %0, %1, %2;" : "=r"(r) : "r"(addr), "r"(cta)); return r; }
__device__ __forceinline__ void mbar_arrive_remote(uint32_t raddr) { asm volatile("mbarrier.arrive.shared::cluster.b64 _, [%0];" ::"r"(raddr) : "memory"); }
__device__ __forceinline__ void mbar_wait(uint32_t bar, uint32_t parity) {
  asm volatile("{\n.reg .pred p;\n.reg .u32 c;\nmov.u32 c, 0;\nWL:\nmbarrier.try_wait.parity.shared::cta.b64 p, [%0], %1;\n@p bra WD;\nadd.u32 c, c, 1;\n"
               "setp.lt.u32 p, c, 4194304;\n@p bra WL;\ntrap;\nWD:\n}\n" ::"r"(bar), "r"(parity) : "memory");
}
__device__ __forceinline__ void tma_load_2d(uint32_t dst, const void* tmap, int c0, int c1, uint32_t bar) {
  asm volatile("cp.async.bulk.tensor.2d.shared::cluster.global.mbarrier::complete_tx::bytes [%0], [%1, {%3, %4}], [%2];" ::"r"(dst), "l"(tmap), "r"(bar), "r"(c0), "r"(c1) : "memory");
}
__device__ __forceinline__ void tma_load_3d(uint32_t dst, const void* tmap, int c0, int c1, int c2, uint32_t bar) {
  asm volatile("cp.async.bulk.tensor.3d.shared::cluster.global.mbarrier::complete_tx::bytes [%0], [%1, {%3, %4, %5}], [%2];" ::"r"(dst), "l"(tmap), "r"(bar), "r"(c0), "r"(c1), "r"(c2) : "memory");
}
__device__ __forceinline__ void tma_load_2d_mc(uint32_t dst, const void* tmap, int c0, int c1, uint32_t bar, uint16_t mask) {
  asm volatile("cp.async.bulk.tensor.2d.shared::cluster.global.mbarrier::complete_tx::bytes.multicast::cluster [%0], [%1, {%3, %4}], [%2], %5;" ::"r"(dst), "l"(tmap), "r"(bar), "r"(c0), "r"(c1), "h"(mask) : "memory");
}
__device__ __forceinline__ void tmap_prefetch(const void* tmap) { asm volatile("prefetch.tensormap [%0];" ::"l"(tmap) : "memory"); }
__device__ __forceinline__ void tma_store_2d(const void* tmap, uint32_t src, int c0, int c1) {
  asm volatile("cp.async.bulk.tensor.2d.global.shared::cta.bulk_group [%0, {%2, %3}], [%1];" ::"l"(tmap), "r"(src), "r"(c0), "r"(c1) : "memory");
}
__device__ __forceinline__ void bulk_load(uint32_t dst, const void* src, uint32_t bytes, uint32_t bar) {
  asm volatile("cp.async.bulk.shared::cluster.global.mbarrier::complete_tx::bytes [%0], [%1], %2, [%3];" ::"r"(dst), "l"(src), "r"(bytes), "r"(bar) : "memory");
}
__device__ __forceinline__ void bulk_store(void* dst, uint32_t src, uint32_t bytes) {
  asm volatile("cp.async.bulk.global.shared::cta.bulk_group [%0], [%1], %2;" ::"l"(dst), "r"(src), "r"(bytes) : "memory");
}
__device__ __forceinline__ void l2_prefetch(const void* p, uint32_t bytes) { asm volatile("cp.async.bulk.prefetch.L2.global [%0], %1;" ::"l"(p), "r"(bytes) : "memory"); }
__device__ __forceinline__ void bulk_commit() { asm volatile("cp.async.bulk.commit_group;" ::: "memory"); }
__device__ __forceinline__ void bulk_wait_all() { asm volatile("cp.async.bulk.wait_group 0;" ::: "memory"); }
__device__ __forceinline__ void bulk_wait_read() { asm volatile("cp.async.bulk.wait_group.read 0;" ::: "memory"); }
__device__ __forceinline__ void fence_async_smem() { asm volatile("fence.proxy.async.shared::cta;" ::: "memory"); }
__device__ __forceinline__ void wg_fence() { asm volatile("wgmma.fence.sync.aligned;" ::: "memory"); }
__device__ __forceinline__ void wg_commit() { asm volatile("wgmma.commit_group.sync.aligned;" ::: "memory"); }
template <int N> __device__ __forceinline__ void wg_wait() { asm volatile("wgmma.wait_group.sync.aligned %0;" ::"n"(N) : "memory"); }
template <int N> __device__ __forceinline__ void fence_regs(float* d) {
#pragma unroll
  for (int i = 0; i < N; i++) asm volatile("" : "+f"(d[i])::"memory");
}
__device__ __forceinline__ void bar_sync(int id, int n) { asm volatile("bar.sync %0, %1;" ::"r"(id), "r"(n) : "memory"); }
__device__ __forceinline__ void bar_arrive(int id, int n) { asm volatile("bar.arrive %0, %1;" ::"r"(id), "r"(n) : "memory"); }
__device__ __forceinline__ void pdl_wait() { asm volatile("griddepcontrol.wait;" ::: "memory"); }
__device__ __forceinline__ void pdl_launch() { asm volatile("griddepcontrol.launch_dependents;" ::: "memory"); }
__device__ __forceinline__ constexpr uint64_t desc_hi(uint32_t lbo, uint32_t sbo, uint32_t swz) {
  return ((uint64_t)(lbo >> 4) << 16) | ((uint64_t)(sbo >> 4) << 32) | ((uint64_t)swz << 62);
}
__device__ __forceinline__ uint64_t mkdesc(uint32_t addr, uint64_t hi) { return hi | (uint64_t)((addr & 0x3FFFFu) >> 4); }
__device__ __forceinline__ uint32_t pack_bf16(float lo, float hi) { uint32_t r; asm("cvt.rn.bf16x2.f32 %0, %1, %2;" : "=r"(r) : "f"(hi), "f"(lo)); return r; }
__device__ __forceinline__ float bf_lo(uint32_t v) { return __uint_as_float(v << 16); }
__device__ __forceinline__ float bf_hi(uint32_t v) { return __uint_as_float(v & 0xFFFF0000u); }
__device__ __forceinline__ float bf_round(float x) { return __bfloat162float(__float2bfloat16_rn(x)); }
__device__ __forceinline__ uint32_t hmul2(uint32_t a, uint32_t b) { uint32_t r; asm("mul.rn.bf16x2 %0, %1, %2;" : "=r"(r) : "r"(a), "r"(b)); return r; }
__device__ __forceinline__ uint32_t hadd2(uint32_t a, uint32_t b) { uint32_t r; asm("add.rn.bf16x2 %0, %1, %2;" : "=r"(r) : "r"(a), "r"(b)); return r; }
__device__ __forceinline__ uint32_t hsub2(uint32_t a, uint32_t b) { uint32_t r; asm("sub.rn.bf16x2 %0, %1, %2;" : "=r"(r) : "r"(a), "r"(b)); return r; }
__device__ __forceinline__ uint32_t prmt(uint32_t a, uint32_t b, uint32_t s) { uint32_t r; asm("prmt.b32 %0, %1, %2, %3;" : "=r"(r) : "r"(a), "r"(b), "r"(s)); return r; }
__device__ __forceinline__ uint4 lds128(uint32_t a) { uint4 v; asm volatile("ld.shared.v4.u32 {%0,%1,%2,%3}, [%4];" : "=r"(v.x), "=r"(v.y), "=r"(v.z), "=r"(v.w) : "r"(a) : "memory"); return v; }
__device__ __forceinline__ float4 lds128f(uint32_t a) { float4 v; asm volatile("ld.shared.v4.f32 {%0,%1,%2,%3}, [%4];" : "=f"(v.x), "=f"(v.y), "=f"(v.z), "=f"(v.w) : "r"(a) : "memory"); return v; }
__device__ __forceinline__ uint2 lds64(uint32_t a) { uint2 v; asm volatile("ld.shared.v2.u32 {%0,%1}, [%2];" : "=r"(v.x), "=r"(v.y) : "r"(a) : "memory"); return v; }
__device__ __forceinline__ float2 lds64f(uint32_t a) { float2 v; asm volatile("ld.shared.v2.f32 {%0,%1}, [%2];" : "=f"(v.x), "=f"(v.y) : "r"(a) : "memory"); return v; }
__device__ __forceinline__ uint32_t lds32(uint32_t a) { uint32_t v; asm volatile("ld.shared.u32 %0, [%1];" : "=r"(v) : "r"(a) : "memory"); return v; }
__device__ __forceinline__ float lds32f(uint32_t a) { float v; asm volatile("ld.shared.f32 %0, [%1];" : "=f"(v) : "r"(a) : "memory"); return v; }
__device__ __forceinline__ uint32_t lds16(uint32_t a) { uint16_t v; asm volatile("ld.shared.u16 %0, [%1];" : "=h"(v) : "r"(a) : "memory"); return v; }
__device__ __forceinline__ void sts128(uint32_t a, uint4 v) { asm volatile("st.shared.v4.u32 [%0], {%1,%2,%3,%4};" ::"r"(a), "r"(v.x), "r"(v.y), "r"(v.z), "r"(v.w) : "memory"); }
__device__ __forceinline__ void sts64(uint32_t a, uint32_t x, uint32_t y) { asm volatile("st.shared.v2.u32 [%0], {%1,%2};" ::"r"(a), "r"(x), "r"(y) : "memory"); }
__device__ __forceinline__ void sts64f(uint32_t a, float x, float y) { asm volatile("st.shared.v2.f32 [%0], {%1,%2};" ::"r"(a), "f"(x), "f"(y) : "memory"); }
__device__ __forceinline__ void sts32(uint32_t a, uint32_t x) { asm volatile("st.shared.u32 [%0], %1;" ::"r"(a), "r"(x) : "memory"); }
__device__ __forceinline__ void sts16(uint32_t a, uint32_t x) { asm volatile("st.shared.u16 [%0], %1;" ::"r"(a), "h"((uint16_t)x) : "memory"); }
__device__ __forceinline__ void sts32f(uint32_t a, float x) { asm volatile("st.shared.f32 [%0], %1;" ::"r"(a), "f"(x) : "memory"); }
__device__ __forceinline__ void ldsm4(uint32_t a, uint32_t& r0, uint32_t& r1, uint32_t& r2, uint32_t& r3) {
  asm volatile("ldmatrix.sync.aligned.m8n8.x4.shared.b16 {%0,%1,%2,%3}, [%4];" : "=r"(r0), "=r"(r1), "=r"(r2), "=r"(r3) : "r"(a) : "memory");
}
__device__ __forceinline__ void ldsm4t(uint32_t a, uint32_t& r0, uint32_t& r1, uint32_t& r2, uint32_t& r3) {
  asm volatile("ldmatrix.sync.aligned.m8n8.x4.trans.shared.b16 {%0,%1,%2,%3}, [%4];" : "=r"(r0), "=r"(r1), "=r"(r2), "=r"(r3) : "r"(a) : "memory");
}
__device__ __forceinline__ void stsm4(uint32_t a, uint32_t r0, uint32_t r1, uint32_t r2, uint32_t r3) {
  asm volatile("stmatrix.sync.aligned.m8n8.x4.shared.b16 [%0], {%1,%2,%3,%4};" ::"r"(a), "r"(r0), "r"(r1), "r"(r2), "r"(r3) : "memory");
}
__device__ __forceinline__ void stsm4t(uint32_t a, uint32_t r0, uint32_t r1, uint32_t r2, uint32_t r3) {
  asm volatile("stmatrix.sync.aligned.m8n8.x4.trans.shared.b16 [%0], {%1,%2,%3,%4};" ::"r"(a), "r"(r0), "r"(r1), "r"(r2), "r"(r3) : "memory");
}
__device__ __forceinline__ void mma16816(float* c, uint32_t a0, uint32_t a1, uint32_t a2, uint32_t a3, uint32_t b0, uint32_t b1) {
  asm volatile("mma.sync.aligned.m16n8k16.row.col.f32.bf16.bf16.f32 {%0,%1,%2,%3}, {%4,%5,%6,%7}, {%8,%9}, {%0,%1,%2,%3};"
               : "+f"(c[0]), "+f"(c[1]), "+f"(c[2]), "+f"(c[3]) : "r"(a0), "r"(a1), "r"(a2), "r"(a3), "r"(b0), "r"(b1));
}
__device__ __forceinline__ uint4 ldg128_nc(const void* p) { uint4 v; asm volatile("ld.global.nc.L1::no_allocate.v4.u32 {%0,%1,%2,%3}, [%4];" : "=r"(v.x), "=r"(v.y), "=r"(v.z), "=r"(v.w) : "l"(p)); return v; }
__device__ __forceinline__ uint2 ldg64_nc(const void* p) { uint2 v; asm volatile("ld.global.nc.L1::no_allocate.v2.u32 {%0,%1}, [%2];" : "=r"(v.x), "=r"(v.y) : "l"(p)); return v; }
__device__ __forceinline__ uint32_t ldg32_nc(const void* p) { uint32_t v; asm volatile("ld.global.nc.u32 %0, [%1];" : "=r"(v) : "l"(p)); return v; }
__device__ __forceinline__ uint32_t ldg16_nc(const void* p) { uint16_t v; asm volatile("ld.global.nc.u16 %0, [%1];" : "=h"(v) : "l"(p)); return v; }
__device__ __forceinline__ uint4 ldg128_cg(const void* p) { uint4 v; asm volatile("ld.global.cg.v4.u32 {%0,%1,%2,%3}, [%4];" : "=r"(v.x), "=r"(v.y), "=r"(v.z), "=r"(v.w) : "l"(p) : "memory"); return v; }
__device__ __forceinline__ void st_rlx64x(void* p, uint32_t x, uint32_t y) { asm volatile("st.relaxed.gpu.global.b64 [%0], %1;" ::"l"(p), "l"((uint64_t)x | ((uint64_t)y << 32)) : "memory"); }
__device__ __forceinline__ void st_rlx32(void* p, uint32_t x) { asm volatile("st.relaxed.gpu.global.u32 [%0], %1;" ::"l"(p), "r"(x) : "memory"); }
__device__ __forceinline__ uint32_t ld_rlx32(const void* p) { uint32_t v; asm volatile("ld.relaxed.gpu.global.u32 %0, [%1];" : "=r"(v) : "l"(p) : "memory"); return v; }
__device__ __forceinline__ uint2 ld_rlx64(const void* p) {
  uint64_t a; asm volatile("ld.relaxed.gpu.global.b64 %0, [%1];" : "=l"(a) : "l"(p) : "memory");
  return make_uint2((uint32_t)a, (uint32_t)(a >> 32));
}
__device__ __forceinline__ uint4 ld_rlx2x64(const void* p) {
  uint64_t a, b; asm volatile("ld.relaxed.gpu.global.v2.b64 {%0,%1}, [%2];" : "=l"(a), "=l"(b) : "l"(p) : "memory");
  return make_uint4((uint32_t)a, (uint32_t)(a >> 32), (uint32_t)b, (uint32_t)(b >> 32));
}
__device__ __forceinline__ float rcp_fast(float x) { float r; asm("rcp.approx.ftz.f32 %0, %1;" : "=f"(r) : "f"(x)); return r; }
__device__ __forceinline__ float ln_den(float var) { float r; asm("sqrt.approx.ftz.f32 %0, %1;" : "=f"(r) : "f"(bf_round(bf_round(var) + 1e-5f))); return bf_round(r); }
__device__ __forceinline__ float ln_rden(float var) { return rcp_fast(ln_den(var)); }
#define PTX2(i)
#define PT(k, role, i)
#define PTX(i)
__device__ __forceinline__ void wgmma_rs_n16(float* d, uint32_t a0, uint32_t a1, uint32_t a2, uint32_t a3, uint64_t db, int sc){
  asm volatile("{\n.reg .pred p;\nsetp.ne.b32 p, %13, 0;\nwgmma.mma_async.sync.aligned.m64n16k16.f32.bf16.bf16 {%0,%1,%2,%3,%4,%5,%6,%7}, {%8,%9,%10,%11}, %12, p, 1, 1, 0;\n}\n"
   : "+f"(d[0]),"+f"(d[1]),"+f"(d[2]),"+f"(d[3]),"+f"(d[4]),"+f"(d[5]),"+f"(d[6]),"+f"(d[7]) : "r"(a0), "r"(a1), "r"(a2), "r"(a3), "l"(db), "r"(sc));
}
__device__ __forceinline__ void wgmma_rs_n24(float* d, uint32_t a0, uint32_t a1, uint32_t a2, uint32_t a3, uint64_t db, int sc){
  asm volatile("{\n.reg .pred p;\nsetp.ne.b32 p, %17, 0;\nwgmma.mma_async.sync.aligned.m64n24k16.f32.bf16.bf16 {%0,%1,%2,%3,%4,%5,%6,%7,%8,%9,%10,%11}, {%12,%13,%14,%15}, %16, p, 1, 1, 0;\n}\n"
   : "+f"(d[0]),"+f"(d[1]),"+f"(d[2]),"+f"(d[3]),"+f"(d[4]),"+f"(d[5]),"+f"(d[6]),"+f"(d[7]),"+f"(d[8]),"+f"(d[9]),"+f"(d[10]),"+f"(d[11]) : "r"(a0), "r"(a1), "r"(a2), "r"(a3), "l"(db), "r"(sc));
}
__device__ __forceinline__ void wgmma_rs_n32(float* d, uint32_t a0, uint32_t a1, uint32_t a2, uint32_t a3, uint64_t db, int sc){
  asm volatile("{\n.reg .pred p;\nsetp.ne.b32 p, %21, 0;\nwgmma.mma_async.sync.aligned.m64n32k16.f32.bf16.bf16 {%0,%1,%2,%3,%4,%5,%6,%7,%8,%9,%10,%11,%12,%13,%14,%15}, {%16,%17,%18,%19}, %20, p, 1, 1, 0;\n}\n"
   : "+f"(d[0]),"+f"(d[1]),"+f"(d[2]),"+f"(d[3]),"+f"(d[4]),"+f"(d[5]),"+f"(d[6]),"+f"(d[7]),"+f"(d[8]),"+f"(d[9]),"+f"(d[10]),"+f"(d[11]),"+f"(d[12]),"+f"(d[13]),"+f"(d[14]),"+f"(d[15]) : "r"(a0), "r"(a1), "r"(a2), "r"(a3), "l"(db), "r"(sc));
}
__device__ __forceinline__ void wgmma_rs_n64(float* d, uint32_t a0, uint32_t a1, uint32_t a2, uint32_t a3, uint64_t db, int sc){
  asm volatile("{\n.reg .pred p;\nsetp.ne.b32 p, %37, 0;\nwgmma.mma_async.sync.aligned.m64n64k16.f32.bf16.bf16 {%0,%1,%2,%3,%4,%5,%6,%7,%8,%9,%10,%11,%12,%13,%14,%15,%16,%17,%18,%19,%20,%21,%22,%23,%24,%25,%26,%27,%28,%29,%30,%31}, {%32,%33,%34,%35}, %36, p, 1, 1, 0;\n}\n"
   : "+f"(d[0]),"+f"(d[1]),"+f"(d[2]),"+f"(d[3]),"+f"(d[4]),"+f"(d[5]),"+f"(d[6]),"+f"(d[7]),"+f"(d[8]),"+f"(d[9]),"+f"(d[10]),"+f"(d[11]),"+f"(d[12]),"+f"(d[13]),"+f"(d[14]),"+f"(d[15]),"+f"(d[16]),"+f"(d[17]),"+f"(d[18]),"+f"(d[19]),"+f"(d[20]),"+f"(d[21]),"+f"(d[22]),"+f"(d[23]),"+f"(d[24]),"+f"(d[25]),"+f"(d[26]),"+f"(d[27]),"+f"(d[28]),"+f"(d[29]),"+f"(d[30]),"+f"(d[31]) : "r"(a0), "r"(a1), "r"(a2), "r"(a3), "l"(db), "r"(sc));
}
__device__ __forceinline__ void wgmma_rs_n112_tb(float* d, uint32_t a0, uint32_t a1, uint32_t a2, uint32_t a3, uint64_t db, int sc){
  asm volatile("{\n.reg .pred p;\nsetp.ne.b32 p, %61, 0;\nwgmma.mma_async.sync.aligned.m64n112k16.f32.bf16.bf16 {%0,%1,%2,%3,%4,%5,%6,%7,%8,%9,%10,%11,%12,%13,%14,%15,%16,%17,%18,%19,%20,%21,%22,%23,%24,%25,%26,%27,%28,%29,%30,%31,%32,%33,%34,%35,%36,%37,%38,%39,%40,%41,%42,%43,%44,%45,%46,%47,%48,%49,%50,%51,%52,%53,%54,%55}, {%56,%57,%58,%59}, %60, p, 1, 1, 1;\n}\n"
   : "+f"(d[0]),"+f"(d[1]),"+f"(d[2]),"+f"(d[3]),"+f"(d[4]),"+f"(d[5]),"+f"(d[6]),"+f"(d[7]),"+f"(d[8]),"+f"(d[9]),"+f"(d[10]),"+f"(d[11]),"+f"(d[12]),"+f"(d[13]),"+f"(d[14]),"+f"(d[15]),"+f"(d[16]),"+f"(d[17]),"+f"(d[18]),"+f"(d[19]),"+f"(d[20]),"+f"(d[21]),"+f"(d[22]),"+f"(d[23]),"+f"(d[24]),"+f"(d[25]),"+f"(d[26]),"+f"(d[27]),"+f"(d[28]),"+f"(d[29]),"+f"(d[30]),"+f"(d[31]),"+f"(d[32]),"+f"(d[33]),"+f"(d[34]),"+f"(d[35]),"+f"(d[36]),"+f"(d[37]),"+f"(d[38]),"+f"(d[39]),"+f"(d[40]),"+f"(d[41]),"+f"(d[42]),"+f"(d[43]),"+f"(d[44]),"+f"(d[45]),"+f"(d[46]),"+f"(d[47]),"+f"(d[48]),"+f"(d[49]),"+f"(d[50]),"+f"(d[51]),"+f"(d[52]),"+f"(d[53]),"+f"(d[54]),"+f"(d[55]) : "r"(a0), "r"(a1), "r"(a2), "r"(a3), "l"(db), "r"(sc));
}
template<int TA,int TB> __device__ __forceinline__ void wgmma_ss_n112(float* d, uint64_t da, uint64_t db, int sc){
  asm volatile("{\n.reg .pred p;\nsetp.ne.b32 p, %58, 0;\nwgmma.mma_async.sync.aligned.m64n112k16.f32.bf16.bf16 {%0,%1,%2,%3,%4,%5,%6,%7,%8,%9,%10,%11,%12,%13,%14,%15,%16,%17,%18,%19,%20,%21,%22,%23,%24,%25,%26,%27,%28,%29,%30,%31,%32,%33,%34,%35,%36,%37,%38,%39,%40,%41,%42,%43,%44,%45,%46,%47,%48,%49,%50,%51,%52,%53,%54,%55}, %56, %57, p, 1, 1, %59, %60;\n}\n"
   : "+f"(d[0]),"+f"(d[1]),"+f"(d[2]),"+f"(d[3]),"+f"(d[4]),"+f"(d[5]),"+f"(d[6]),"+f"(d[7]),"+f"(d[8]),"+f"(d[9]),"+f"(d[10]),"+f"(d[11]),"+f"(d[12]),"+f"(d[13]),"+f"(d[14]),"+f"(d[15]),"+f"(d[16]),"+f"(d[17]),"+f"(d[18]),"+f"(d[19]),"+f"(d[20]),"+f"(d[21]),"+f"(d[22]),"+f"(d[23]),"+f"(d[24]),"+f"(d[25]),"+f"(d[26]),"+f"(d[27]),"+f"(d[28]),"+f"(d[29]),"+f"(d[30]),"+f"(d[31]),"+f"(d[32]),"+f"(d[33]),"+f"(d[34]),"+f"(d[35]),"+f"(d[36]),"+f"(d[37]),"+f"(d[38]),"+f"(d[39]),"+f"(d[40]),"+f"(d[41]),"+f"(d[42]),"+f"(d[43]),"+f"(d[44]),"+f"(d[45]),"+f"(d[46]),"+f"(d[47]),"+f"(d[48]),"+f"(d[49]),"+f"(d[50]),"+f"(d[51]),"+f"(d[52]),"+f"(d[53]),"+f"(d[54]),"+f"(d[55]) : "l"(da), "l"(db), "r"(sc), "n"(TA), "n"(TB));
}
template<int TA,int TB> __device__ __forceinline__ void wgmma_ss_n224(float* d, uint64_t da, uint64_t db, int sc){
  asm volatile("{\n.reg .pred p;\nsetp.ne.b32 p, %114, 0;\nwgmma.mma_async.sync.aligned.m64n224k16.f32.bf16.bf16 {%0,%1,%2,%3,%4,%5,%6,%7,%8,%9,%10,%11,%12,%13,%14,%15,%16,%17,%18,%19,%20,%21,%22,%23,%24,%25,%26,%27,%28,%29,%30,%31,%32,%33,%34,%35,%36,%37,%38,%39,%40,%41,%42,%43,%44,%45,%46,%47,%48,%49,%50,%51,%52,%53,%54,%55,%56,%57,%58,%59,%60,%61,%62,%63,%64,%65,%66,%67,%68,%69,%70,%71,%72,%73,%74,%75,%76,%77,%78,%79,%80,%81,%82,%83,%84,%85,%86,%87,%88,%89,%90,%91,%92,%93,%94,%95,%96,%97,%98,%99,%100,%101,%102,%103,%104,%105,%106,%107,%108,%109,%110,%111}, %112, %113, p, 1, 1, %115, %116;\n}\n"
   : "+f"(d[0]),"+f"(d[1]),"+f"(d[2]),"+f"(d[3]),"+f"(d[4]),"+f"(d[5]),"+f"(d[6]),"+f"(d[7]),"+f"(d[8]),"+f"(d[9]),"+f"(d[10]),"+f"(d[11]),"+f"(d[12]),"+f"(d[13]),"+f"(d[14]),"+f"(d[15]),"+f"(d[16]),"+f"(d[17]),"+f"(d[18]),"+f"(d[19]),"+f"(d[20]),"+f"(d[21]),"+f"(d[22]),"+f"(d[23]),"+f"(d[24]),"+f"(d[25]),"+f"(d[26]),"+f"(d[27]),"+f"(d[28]),"+f"(d[29]),"+f"(d[30]),"+f"(d[31]),"+f"(d[32]),"+f"(d[33]),"+f"(d[34]),"+f"(d[35]),"+f"(d[36]),"+f"(d[37]),"+f"(d[38]),"+f"(d[39]),"+f"(d[40]),"+f"(d[41]),"+f"(d[42]),"+f"(d[43]),"+f"(d[44]),"+f"(d[45]),"+f"(d[46]),"+f"(d[47]),"+f"(d[48]),"+f"(d[49]),"+f"(d[50]),"+f"(d[51]),"+f"(d[52]),"+f"(d[53]),"+f"(d[54]),"+f"(d[55]),"+f"(d[56]),"+f"(d[57]),"+f"(d[58]),"+f"(d[59]),"+f"(d[60]),"+f"(d[61]),"+f"(d[62]),"+f"(d[63]),"+f"(d[64]),"+f"(d[65]),"+f"(d[66]),"+f"(d[67]),"+f"(d[68]),"+f"(d[69]),"+f"(d[70]),"+f"(d[71]),"+f"(d[72]),"+f"(d[73]),"+f"(d[74]),"+f"(d[75]),"+f"(d[76]),"+f"(d[77]),"+f"(d[78]),"+f"(d[79]),"+f"(d[80]),"+f"(d[81]),"+f"(d[82]),"+f"(d[83]),"+f"(d[84]),"+f"(d[85]),"+f"(d[86]),"+f"(d[87]),"+f"(d[88]),"+f"(d[89]),"+f"(d[90]),"+f"(d[91]),"+f"(d[92]),"+f"(d[93]),"+f"(d[94]),"+f"(d[95]),"+f"(d[96]),"+f"(d[97]),"+f"(d[98]),"+f"(d[99]),"+f"(d[100]),"+f"(d[101]),"+f"(d[102]),"+f"(d[103]),"+f"(d[104]),"+f"(d[105]),"+f"(d[106]),"+f"(d[107]),"+f"(d[108]),"+f"(d[109]),"+f"(d[110]),"+f"(d[111]) : "l"(da), "l"(db), "r"(sc), "n"(TA), "n"(TB));
}

struct KMap { uint32_t v[640]; };
constexpr int kv_ij(int i, int j) { return i * 42 + j; }
constexpr int KV_ZERO = 41;
constexpr int kv_entry(int v) {
  return v < 256 ? kv_ij(v % 8, v / 8)
       : v < 512 ? kv_ij(8 + (v % 8) / 2, (v - 256) / 8)
       : v < 1024 ? kv_ij(12 + 2 * ((v - 512) / 256) + (v % 8) / 4, ((v - 512) % 256) / 8)
       : v < 2048 ? kv_ij(16 + (v - 1024) / 256, ((v - 1024) % 256) / 8)
       : kv_ij(20, 0);
}
constexpr int round_pos(int x) {
  int step = x < 256 ? 1 : x < 512 ? 2 : 4;
  int q = x / step, r = x % step;
  if (step > 1 && (2 * r > step || (2 * r == step && (q & 1)))) q++;
  return q * step;
}
constexpr int z_direct(int half, int z) {
  const int x = z - 31 + 256 * half;
  return (x >= 256 * half && x <= (half ? 514 : 255)) ? kv_entry(round_pos(x)) : KV_ZERO;
}
constexpr int z_tail(int z) {
  if (z < 128) { int a = z - 62; return (a >= 1 && a <= 63) ? kv_entry(512 + 8 * a) : KV_ZERO; }
  if (z < 256) { int a = z - 128 - 63; return (a >= 0 && a <= 63) ? kv_entry(516 + 8 * a) : KV_ZERO; }
  int a = z - 256 - 62; return (a >= 1 && a <= 128) ? kv_entry(1024 + 8 * a) : KV_ZERO;
}
constexpr int z_entry(int w, int e) { return w < 336 ? z_direct(w & 1, 2 * (w >> 1) + e) : z_tail(2 * (w - 336) + e); }
constexpr KMap make_kmap() {
  KMap m{};
  for (int w = 0; w < 640; w++) m.v[w] = (uint32_t)z_entry(w, 0) | ((uint32_t)z_entry(w, 1) << 10) | ((uint32_t)z_entry(w, 2) << 20);
  return m;
}
__device__ __align__(16) const KMap g_kmap = make_kmap();

constexpr int K1_TP = 272, K1_TA1 = 16 * K1_TP, K1_TW = K1_TA1 + 21 * K1_TP, K1_TG = 4 * K1_TW;
constexpr int K1_KV = K1_TA1, K1_Z0 = K1_TW + K1_TA1, K1_Z1 = K1_Z0 + 2624, K1_S = 2 * K1_TW, K1_Y0 = 0, K1_Y2 = K1_S + 11520;
constexpr int K1_S5 = 0, K1_S3 = 3456, K1_EO = 6912;
constexpr int K1_H = 4 * K1_TG, K1_CS = 1184, K1_HSZ = 4 * K1_CS;
constexpr int K1_U = K1_H + 4 * K1_HSZ, K1_KM = K1_U + 16384, K1_MISC = K1_KM + 10240;
constexpr int K1_AUXR = 4096, K1_AUXB = 20480;
constexpr int K1_SMEM = K1_MISC + 64;
static_assert(K1_Z1 + 2624 <= K1_S && K1_Y2 + 6528 <= K1_TG && K1_Y0 + 9200 <= K1_Z0 && K1_SMEM <= 232448 && K1_AUXB + 3 * 57344 <= K1_SMEM, "");

struct cplx { float r, i; };
__device__ __forceinline__ cplx cmul(cplx a, cplx b) { cplx c; c.r = fmaf(a.r, b.r, -a.i * b.i); c.i = fmaf(a.r, b.i, a.i * b.r); return c; }
__device__ __forceinline__ cplx csq(cplx a) { cplx c; c.r = fmaf(a.r, a.r, -a.i * a.i); c.i = (a.r + a.r) * a.i; return c; }
__device__ __forceinline__ cplx cexp_p(float ar, float ai, float p) {
  float m; asm("ex2.approx.ftz.f32 %0, %1;" : "=f"(m) : "f"(ar * p * 1.4426950408889634f));
  float t = ai * p * 0.15915494309189535f;
  t = (t - rintf(t)) * 6.283185307179586f;
  cplx c; c.r = m * __cosf(t); c.i = m * __sinf(t); return c;
}
__device__ __forceinline__ uint32_t h_chunk(uint32_t hb, int q) { return hb + (3 - (q & 3)) * K1_CS + ((q >> 2) + 10) * 16; }
__device__ __forceinline__ void unpack_rev(uint4 v, float* o) {
  o[7] = bf_lo(v.x); o[6] = bf_hi(v.x); o[5] = bf_lo(v.y); o[4] = bf_hi(v.y);
  o[3] = bf_lo(v.z); o[2] = bf_hi(v.z); o[1] = bf_lo(v.w); o[0] = bf_hi(v.w);
}

constexpr uint32_t K1_DLY_M = 3800, K1_DLY_P = 3000;
struct K1Args {
  const bf16 *u, *Are, *Aim, *Bre, *Bim, *Cre, *Cim, *logdt, *dskip, *c, *w_mod;
  const unsigned int* epoch; const uint32_t* kmap; uint2* stat1; uint2* uT; uint32_t* mod;
  const bf16* w_in;
  bf16* x1T; uint8_t *wimg, *waug;
};

__device__ __forceinline__ void ln1_part(uint4 lo, uint4 hi, uint32_t part, uint2* uT, int cta, int warp, int lane) {
  if (warp < 14) {
    uint2* o = uT + (warp * 8 + (lane & 3) * 2) * L_ + cta * 16 + (lane >> 2);
    o[0] = make_uint2(lo.x, lo.y); o[8] = make_uint2(hi.x, hi.y); o[L_] = make_uint2(lo.z, lo.w); o[L_ + 8] = make_uint2(hi.z, hi.w);
    float cs[4] = {0.f, 0.f, 0.f, 0.f}, ql[4] = {0.f, 0.f, 0.f, 0.f}, qh[4] = {0.f, 0.f, 0.f, 0.f};
    mma16816(cs, lo.x, hi.x, lo.y, hi.y, 0x3F803F80u, 0x3F803F80u);
    mma16816(ql, lo.x, hi.x, lo.y, hi.y, lo.x, lo.y);
    mma16816(qh, lo.x, hi.x, lo.y, hi.y, hi.x, hi.y);
    mma16816(cs, lo.z, hi.z, lo.w, hi.w, 0x3F803F80u, 0x3F803F80u);
    mma16816(ql, lo.z, hi.z, lo.w, hi.w, lo.z, lo.w);
    mma16816(qh, lo.z, hi.z, lo.w, hi.w, hi.z, hi.w);
    const int g = lane >> 2;
    if ((lane & 3) == (g >> 1)) {
      sts64f(part + warp * 128 + g * 8, cs[0], (g & 1) ? ql[1] : ql[0]);
      sts64f(part + warp * 128 + 64 + g * 8, cs[2], (g & 1) ? qh[3] : qh[2]);
    }
    __syncwarp();
    bar_arrive(1, 480);
  }
}
__device__ __forceinline__ void ln1_fin(uint32_t part, uint2* stat, int lane, uint32_t tag) {
  bar_sync(1, 480);
  float2 p[7];
#pragma unroll
  for (int i = 0; i < 7; i++) p[i] = lds64f(part + i * 256 + lane * 8);
  float s = ((p[0].x + p[1].x) + (p[2].x + p[3].x)) + ((p[4].x + p[5].x) + p[6].x);
  float q = ((p[0].y + p[1].y) + (p[2].y + p[3].y)) + ((p[4].y + p[5].y) + p[6].y);
  s += __shfl_xor_sync(~0u, s, 16); q += __shfl_xor_sync(~0u, q, 16);
  const float mean = s * (1.0f / D_), var = fmaxf(fmaf(-mean, mean, q * (1.0f / D_)), 0.f);
  PTX(14);
  asm volatile("fence.acq_rel.gpu;" ::: "memory");
  PTX(15);
  if (lane < 16) st_rlx64x(stat + lane, __float_as_uint(bf_round(mean)) | tag, __float_as_uint(ln_rden(var)));
  __syncwarp();
}

__device__ __forceinline__ uint32_t silu2(uint32_t c2) {
  const float a = bf_lo(c2), b = bf_hi(c2);
  return pack_bf16(a * rcp_fast(1.0f + __expf(-a)), b * rcp_fast(1.0f + __expf(-b)));
}

__device__ __forceinline__ void aux_slab(uint32_t dst, const CUtensorMap* tm, int col, uint32_t bar) {
  mbar_expect_tx(bar, 57344);
  tma_load_2d(dst, tm, col, 0, bar);
  tma_load_2d(dst + 28672, tm, col, 224, bar);
}
__device__ __forceinline__ void k1_aux(const K1Args& a, const CUtensorMap* tm_wmod, const CUtensorMap* tm_win, uint32_t sm,
                                       int tid, int warp, int lane, int cta) {
  const uint32_t bar = sm + 3840, sc = sm, clk0 = clock(), buf = sm + K1_AUXB;
  const int ax = cta - 112, cb = ax * 64, c2 = cb + (ax >= 7 ? 4 : 2) * D_;
  const bool domod = ax < 14;
  uint4 ulo = make_uint4(0, 0, 0, 0), uhi = ulo;
  if (warp < 14) { const bf16* p = a.u + (cta * 16 + (lane >> 2)) * D_ + warp * 32 + (lane & 3) * 8; ulo = ldg128_nc(p); uhi = ldg128_nc(p + 8 * D_); }
  const uint32_t tagraw = ldg32_nc(a.epoch);
  if (warp == 14) {
    if (lane == 0) {
#pragma unroll 1
      for (int i = 0; i < 8; i++) mbar_init(bar + 8 * i, 1);
      asm volatile("fence.mbarrier_init.release.cluster;" ::: "memory");
      tmap_prefetch(tm_wmod); tmap_prefetch(tm_win);
    }
    __syncwarp();
    bar_arrive(2, 512);
    if (lane == 0) {
      while ((uint32_t)clock() - clk0 < K1_DLY_M) {}
      if (domod) aux_slab(buf, tm_wmod, cb, bar);
      mbar_wait(bar + 56, 0);
      if (domod) aux_slab(buf + 57344, tm_wmod, cb + 3 * D_, bar + 8);
      aux_slab(buf + 2 * 57344, tm_win, ax * 112, bar + 16);
      if (domod) { mbar_wait(bar + 40, 0); aux_slab(buf, tm_wmod, c2, bar + 32); mbar_wait(bar + 48, 0); }
      aux_slab(buf + 57344, tm_win, ax * 112 + 64, bar + 24);
    }
    return;
  }
  const uint32_t tag = (tagraw + 1u) & 0xFFFFu;
  if (warp == 15) {
    ln1_fin(sm + 2048, a.stat1 + cta * 16, lane, tag);
    bar_sync(2, 512);
    if (lane == 0) mbar_arrive(bar + 56);
    bar_sync(3, 480);
    if (lane == 0) { asm volatile("fence.acq_rel.gpu;" ::: "memory"); pdl_launch(); }
    PTX(13);
    return;
  }
  uint32_t af[2][2] = {{0u, 0u}, {0u, 0u}}, ag[2][2];
  {
    if (lane < 4) {
      const bf16* q = a.c + warp * 16 + 2 * lane;
      af[0][0] = ldg32_nc(q); af[0][1] = ldg32_nc(q + 8); af[1][0] = ldg32_nc(q + 224); af[1][1] = ldg32_nc(q + 232);
    }
    __syncwarp();
    ln1_part(ulo, uhi, sm + 2048, a.uT, cta, warp, lane);
  }
  af[0][0] = silu2(af[0][0]); af[0][1] = silu2(af[0][1]); af[1][0] = silu2(af[1][0]); af[1][1] = silu2(af[1][1]);
  PT(0, warp >> 2, 1);
  bar_sync(2, 512);
#pragma unroll 1
  for (int si = domod ? 0 : 3; si < 5; si++) {
    const int st = (0x32410 >> (4 * si)) & 7;
    const uint32_t red = sm + K1_AUXR + (si & 1) * 8192;
    const bool cs = st == 2 || st == 3;
    if (st == 2) {
      uint32_t vc, it = 0;
      do { vc = ld_rlx32(a.mod + 4 * D_ + tid); if (++it > (1u << 22)) __trap(); } while ((vc & 0xFFFFu) != tag);
      sts16(sc + tid * 2, pack_bf16(1.0f + bf_hi(vc), 0.f));
      bar_sync(4, 448);
      mbar_wait(bar + 16, 0); mbar_wait(bar + 24, 0);
      PT(0, warp >> 2, 5);
      const int nc = (tid % 112) >> 3, rl = (tid / 112) * 8 + (tid & 7);
      uint32_t src = buf + (nc < 8 ? 2 * 57344 : 57344) + rl * 128 + (((nc ^ tid) & 7) << 4), ss = sc + rl * 2;
      uint8_t* dst = a.wimg + ax * 7 * 14336 + nc * 1024 + rl * 16;
#pragma unroll 1
      for (int i = 0; i < 7; i++, src += 64 * 128, ss += 128, dst += 14336) {
        const uint4 v0 = lds128(src), v1 = lds128(src + 32 * 128);
        const uint32_t m0 = lds16(ss) * 0x10001u, m1 = lds16(ss + 64) * 0x10001u;
        *(uint4*)dst = make_uint4(hmul2(v0.x, m0), hmul2(v0.y, m0), hmul2(v0.z, m0), hmul2(v0.w, m0));
        *(uint4*)(dst + 512) = make_uint4(hmul2(v1.x, m1), hmul2(v1.y, m1), hmul2(v1.z, m1), hmul2(v1.w, m1));
      }
      bar_arrive(3, 480);
      PT(0, warp >> 2, 6);
      if (tid < 168) *(uint4*)(a.waug + ax * 3584 + (tid / 12) * 256 + 64 + (tid % 12) * 16) = make_uint4(0u, 0u, 0u, 0u);
      ag[0][0] = ag[0][1] = ag[1][0] = ag[1][1] = 0u;
      if (lane < 4) {
        const uint32_t k = sc + (warp * 16 + 2 * lane) * 2;
        ag[0][0] = lds32(k); ag[0][1] = lds32(k + 16); ag[1][0] = lds32(k + 448); ag[1][1] = lds32(k + 464);
      } else if (lane < 8) {
#pragma unroll
        for (int i = 0; i < 2; i++) {
          const int k = warp * 16 + 224 * i + 2 * (lane - 4);
          uint2 v0, v1;
          it = 0;
          do {
            v0 = ld_rlx64(a.mod + 3 * D_ + k); v1 = ld_rlx64(a.mod + 3 * D_ + k + 8);
            if (++it > (1u << 22)) __trap();
          } while (((v0.x ^ tag) | (v0.y ^ tag) | (v1.x ^ tag) | (v1.y ^ tag)) & 0xFFFFu);
          ag[i][0] = prmt(v0.x, v0.y, 0x7632); ag[i][1] = prmt(v1.x, v1.y, 0x7632);
        }
      }
      __syncwarp();
    }
    mbar_wait(bar + 8 * st, 0);
    if (st == 0) PT(0, warp >> 2, 3);
    {
      const uint32_t base = buf + ((0x01210 >> (4 * st)) & 3) * 57344 + (warp * 16 + (lane & 7) + (lane >> 4) * 8) * 128;
      float acc[4][4];
      uint32_t b[2][4][4];
#pragma unroll
      for (int n2 = 0; n2 < 4; n2++) {
        const uint32_t ad = base + (((2 * n2 + ((lane >> 3) & 1)) ^ (lane & 7)) << 4);
        ldsm4t(ad, b[0][n2][0], b[0][n2][1], b[0][n2][2], b[0][n2][3]); ldsm4t(ad + 28672, b[1][n2][0], b[1][n2][1], b[1][n2][2], b[1][n2][3]);
      }
      const uint32_t v00 = cs ? ag[0][0] : af[0][0], v01 = cs ? ag[0][1] : af[0][1], v10 = cs ? ag[1][0] : af[1][0], v11 = cs ? ag[1][1] : af[1][1];
#pragma unroll
      for (int n = 0; n < 4; n++) {
        acc[n][0] = acc[n][1] = acc[n][2] = acc[n][3] = 0.f;
        mma16816(acc[n], b[0][n][0], b[0][n][1], b[0][n][2], b[0][n][3], v00, v01);
        mma16816(acc[n], b[1][n][0], b[1][n][1], b[1][n][2], b[1][n][3], v10, v11);
      }
      if (!(lane & 3)) {
#pragma unroll
        for (int n = 0; n < 4; n++) {
          const uint32_t o = red + (warp * 64 + n * 16 + (lane >> 2)) * 4;
          sts32f(o, acc[n][0]); sts32f(o + 32, acc[n][2]); sts32f(o + 4096, acc[n][1]); sts32f(o + 4096 + 32, acc[n][3]);
        }
      }
    }
    bar_sync(4, 448);
    if (st < 2 && tid == 128) mbar_arrive(bar + 40 + 8 * st);
    if (tid < (cs ? 128 : 64)) {
      float v[14];
#pragma unroll
      for (int r = 0; r < 14; r++) v[r] = lds32f(red + (tid >> 6) * 4096 + (r * 64 + (tid & 63)) * 4);
      const float x = (((v[0] + v[1]) + (v[2] + v[3])) + ((v[4] + v[5]) + (v[6] + v[7]))) + (((v[8] + v[9]) + (v[10] + v[11])) + (v[12] + v[13]));
      const float xr = bf_round(x);
      const int n = (st - 2) * 64 + (tid & 63);
      if (!cs) st_rlx32(a.mod + (st == 4 ? c2 : cb + st * 3 * D_) + tid, __float_as_uint(xr) | tag);
      else if (n < 112) {
        uint16_t* dst = (uint16_t*)(a.waug + ax * 3584 + (n >> 3) * 256 + (tid >> 6) * 32) + (n & 7);
        const uint32_t p = pack_bf16(xr, x - xr);
        dst[0] = (uint16_t)p; dst[8] = (uint16_t)(p >> 16);
      }
    }
    if (st == 0) PT(0, warp >> 2, 2);
    if (st == 1) PT(0, warp >> 2, 4);
  }
  PT(0, warp >> 2, 10);
}

__global__ void __launch_bounds__(512, 1) k1_conv(const K1Args a, const __grid_constant__ CUtensorMap tm_wmod, const __grid_constant__ CUtensorMap tm_win) {
  extern __shared__ __align__(1024) uint8_t smem_raw[];
  const uint32_t sm = smem_u32(smem_raw);
  const int tid = threadIdx.x, warp = __shfl_sync(~0u, tid >> 5, 0), lane = tid & 31, cta = blockIdx.x;
  const int g = lane >> 2, t4 = lane & 3;
  const int d0 = cta * 4;
  const uint32_t s_kv1024 = sm + K1_MISC;
  const int wg = warp >> 2, w4 = warp & 3, t = tid & 127;
  PT(0, wg, 0);
  if (cta >= 112) { k1_aux(a, &tm_wmod, &tm_win, sm, tid, warp, lane, cta); return; }
  const uint32_t clk0 = clock();
  uint4 ulo = make_uint4(0, 0, 0, 0), uhi = ulo;
  if (warp < 14) { const bf16* p = a.u + (cta * 16 + g) * D_ + warp * 32 + t4 * 8; ulo = ldg128_nc(p); uhi = ldg128_nc(p + 8 * D_); }
  const uint32_t tagraw = ldg32_nc(a.epoch);
  const int po = (d0 + wg) * NM_ + 2 * t;
  const uint32_t pAre = ldg32_nc(a.Are + po), pAim = ldg32_nc(a.Aim + po), pBre = ldg32_nc(a.Bre + po), pBim = ldg32_nc(a.Bim + po), pCre = ldg32_nc(a.Cre + po), pCim = ldg32_nc(a.Cim + po);
  const uint32_t ldtr = ldg16_nc(a.logdt + d0 + wg);
  if (tid == 448) pdl_launch();
  if (tid < 160) sts128(sm + K1_H + (tid / 10) * K1_CS + (tid % 10) * 16, make_uint4(0, 0, 0, 0));
  if (warp == 14) {
    while ((uint32_t)clock() - clk0 < K1_DLY_P) {}
    if (lane < 4) l2_prefetch((const uint8_t*)a.w_mod + (d0 + lane) * 5376, 1792);
    __syncwarp();
  }
  ln1_part(ulo, uhi, sm + 15 * K1_TW, a.uT, cta, warp, lane);
  if (warp == 15) ln1_fin(sm + 15 * K1_TW, a.stat1 + cta * 16, lane, (tagraw + 1u) & 0xFFFFu);
  PT(0, wg, 13);
  uint32_t km[5];
#pragma unroll
  for (int i = 0; i < 5; i++) km[i] = ldg32_nc(a.kmap + t + 128 * i);
  const float dt = bf_round(expf(bf_lo(ldtr)));
  if (warp == 14 && (pAre ^ pAim ^ pBre ^ pBim ^ pCre ^ pCim) != 0x7FC1FFC3u) {
    if (lane < 4) l2_prefetch((const uint8_t*)a.w_mod + (d0 + lane) * 5376 + 1792, 3584);
    if (lane == 4) l2_prefetch((const uint8_t*)a.w_in + cta * 14336, 14336);
  }
  __syncwarp();
  const uint32_t tag = (tagraw + 1u) & 0xFFFFu;
  PT(0, wg, 1);

  const uint32_t R = sm + wg * K1_TG, ta0 = R + w4 * K1_TW, ta1 = ta0 + K1_TA1;
  float kacc[2][3][4];
#pragma unroll
  for (int i = 0; i < 2; i++)
#pragma unroll
    for (int j = 0; j < 3; j++)
#pragma unroll
      for (int k = 0; k < 4; k++) kacc[i][j][k] = 0.f;
  uint32_t bfr[3][4][4];
  uint4 st01, st23, msa, mca, uqa, uqb;
  {
    cplx E8[2], y[2], E128[2];
#define ST2(base, j, v) sts64((base) + (j) * K1_TP + lane * 8, pack_bf16((v)[0].r, (v)[0].i), pack_bf16((v)[1].r, (v)[1].i))
#define FOR2 _Pragma("unroll") for (int p = 0; p < 2; p++)
    {
      cplx w[2], E1[2], E2[2], E4[2], E256[2], b[2], x[2];
      FOR2 {
        const float ar = dt * (p ? bf_hi(pAre) : bf_lo(pAre)), ai = dt * (p ? bf_hi(pAim) : bf_lo(pAim));
        const cplx db = {dt * (p ? bf_hi(pBre) : bf_lo(pBre)), dt * (p ? bf_hi(pBim) : bf_lo(pBim))};
        const cplx cc = {p ? bf_hi(pCre) : bf_lo(pCre), p ? bf_hi(pCim) : bf_lo(pCim)};
        w[p] = cmul(cc, db);
        w[p].i = -w[p].i;
        E1[p] = cexp_p(ar, -ai, 1.f); E8[p] = cexp_p(ar, ai, 8.f); E128[p] = cexp_p(ar, ai, 128.f);
      }
      FOR2 { E2[p] = csq(E1[p]); E4[p] = csq(E2[p]); E256[p] = csq(E128[p]); E256[p].i = -E256[p].i; b[p] = cmul(w[p], E256[p]); }
      ST2(ta1, 0, w); ST2(ta1, 8, b);
      FOR2 { w[p] = cmul(w[p], E1[p]); x[p] = cmul(b[p], E2[p]); b[p] = cmul(b[p], E256[p]); }
      ST2(ta1, 1, w); ST2(ta1, 9, x); ST2(ta1, 12, b);
      FOR2 { w[p] = cmul(w[p], E1[p]); x[p] = cmul(x[p], E2[p]); y[p] = cmul(b[p], E4[p]); b[p] = cmul(b[p], E256[p]); }
      ST2(ta1, 2, w); ST2(ta1, 10, x); ST2(ta1, 13, y); ST2(ta1, 14, b);
      FOR2 { w[p] = cmul(w[p], E1[p]); x[p] = cmul(x[p], E2[p]); y[p] = cmul(b[p], E4[p]); b[p] = cmul(b[p], E256[p]); }
      ST2(ta1, 3, w); ST2(ta1, 11, x); ST2(ta1, 15, y); ST2(ta1, 16, b);
#pragma unroll
      for (int j = 4; j < 8; j++) {
        FOR2 { w[p] = cmul(w[p], E1[p]); b[p] = cmul(b[p], E256[p]); }
        ST2(ta1, j, w); ST2(ta1, 13 + j, b);
      }
    }
    PT(0, wg, 12);
#pragma unroll
    for (int i = 0; i < 5; i++) sts32(sm + K1_KM + (tid + 512 * i) * 4, km[i]);
    __syncwarp();
    sts64(ta0 + lane * 8, 0x3F80u, 0x3F80u);
    FOR2 y[p] = E8[p];
    ST2(ta0, 1, y);
    const uint32_t bad = ta1 + (lane >> 3) * 16;
#pragma unroll
    for (int j = 2; j < 16; j++) {
      FOR2 y[p] = cmul(y[p], E8[p]);
      ST2(ta0, j, y);
      if (j < 14) {
        const int nt = (j - 2) >> 2, k2 = (j - 2) & 3;
        ldsm4(bad + (nt < 2 ? nt * 8 + (lane & 7) : min(16 + (lane & 7), 20)) * K1_TP + k2 * 64, bfr[nt][k2][0], bfr[nt][k2][1], bfr[nt][k2][2], bfr[nt][k2][3]);
      }
    }
    __syncwarp();
    const uint32_t aad = (lane & 15) * K1_TP + (lane >> 4) * 16;
    FOR2 y[p] = E128[p];
#pragma unroll
    for (int j = 0; j < 16; j++) {
      uint32_t a0, a1, a2, a3;
      if (j == 15) { st01 = ld_rlx2x64(a.stat1 + 4 * tid); st23 = ld_rlx2x64(a.stat1 + 4 * tid + 2); }
      if (!(j & 1)) ldsm4(ta0 + aad + j * 16, a0, a1, a2, a3);
      ST2(ta1, j, y);
      if (j < 15) { FOR2 y[p] = cmul(y[p], E8[p]); }
      if (!(j & 1)) {
#pragma unroll
        for (int nt = 0; nt < 3; nt++) mma16816(kacc[0][nt], a0, a1, a2, a3, bfr[nt][j >> 2][(j & 2)], bfr[nt][j >> 2][(j & 2) + 1]);
      }
    }
    PT(0, wg, 3);
    __syncwarp();
#pragma unroll
    for (int j = 0; j < 8; j++) {
      uint32_t a0, a1, a2, a3;
      ldsm4(ta1 + aad + j * 32, a0, a1, a2, a3);
      if (j < 6) sts64f(ta0 + ((g + 8 * (j & 1)) * 24 + (j >> 1) * 8 + 2 * t4) * 4, kacc[0][j >> 1][2 * (j & 1)], kacc[0][j >> 1][2 * (j & 1) + 1]);
#pragma unroll
      for (int nt = 0; nt < 3; nt++) mma16816(kacc[1][nt], a0, a1, a2, a3, bfr[nt][j >> 1][2 * (j & 1)], bfr[nt][j >> 1][2 * (j & 1) + 1]);
    }
#pragma unroll
    for (int nt = 0; nt < 3; nt++) {
      sts64f(ta0 + ((16 + g) * 24 + nt * 8 + 2 * t4) * 4, kacc[1][nt][0], kacc[1][nt][1]);
      sts64f(ta0 + ((24 + g) * 24 + nt * 8 + 2 * t4) * 4, kacc[1][nt][2], kacc[1][nt][3]);
    }
    for (uint32_t it = 0; ((st01.x ^ tag) | (st01.z ^ tag) | (st23.x ^ tag) | (st23.z ^ tag)) & 0xFFFFu;) {
      st01 = ld_rlx2x64(a.stat1 + 4 * tid); st23 = ld_rlx2x64(a.stat1 + 4 * tid + 2);
      if (++it > (1u << 22)) __trap();
    }
    __syncwarp();
    PT(0, wg, 11);
    uqa = ld_rlx2x64(a.uT + cta * L_ + 4 * tid); uqb = ld_rlx2x64(a.uT + cta * L_ + 4 * tid + 2);
    msa = ld_rlx2x64(a.mod + d0); mca = ld_rlx2x64(a.mod + D_ + d0);
  }
  PT(0, wg, 5);
  bar_sync(2 + wg, 128);
  const uint32_t KV = R + K1_KV;
  {
#pragma unroll
    for (int i = 0; i < 5; i++) km[i] = lds32(sm + K1_KM + (tid + 512 * i) * 4);
    float2 pv[3][4];
#pragma unroll
    for (int i = 0; i < 3; i++)
#pragma unroll
      for (int w = 0; w < 4; w++) pv[i][w] = lds64f(R + w * K1_TW + (t + 128 * i) * 8);
#pragma unroll
    for (int i = 0; i < 3; i++) {
      const float sx = (pv[i][0].x + pv[i][1].x) + (pv[i][2].x + pv[i][3].x), sy = (pv[i][0].y + pv[i][1].y) + (pv[i][2].y + pv[i][3].y);
      const int pr = t + 128 * i, j = pr / 12, ii = 2 * (pr % 12);
      const uint32_t pk = pack_bf16(sx, sy);
      sts16(KV + (ii * 42 + j) * 2, pk); sts16(KV + (ii * 42 + 42 + j) * 2, pk >> 16);
      if (i == 0 && t == 8) sts32f(s_kv1024 + wg * 4, sx);
    }
    if (t == 0) sts16(KV + KV_ZERO * 2, 0u);
  }
  bar_sync(2 + wg, 128);
  uint32_t e0[5], e1[5], e2[5];
#define Z_LOAD(i) { e0[i] = lds16(KV + (km[i] & 1023u) * 2); e1[i] = lds16(KV + ((km[i] >> 10) & 1023u) * 2); e2[i] = lds16(KV + (km[i] >> 20) * 2); }
#define Z_STORE(i) { sts32(R + K1_Z0 + (t + 128 * (i)) * 4, prmt(e0[i], e1[i], 0x5410)); sts32(R + K1_Z1 + (t + 128 * (i)) * 4, prmt(e1[i], e2[i], 0x5410)); }
  Z_LOAD(0) Z_LOAD(1) Z_LOAD(2) Z_LOAD(3) Z_LOAD(4) Z_STORE(0) Z_STORE(1) Z_STORE(2) Z_STORE(3) Z_STORE(4)
  PT(0, wg, 4);
  {
    for (uint32_t it = 0; ((msa.x ^ tag) | (msa.y ^ tag) | (msa.z ^ tag) | (msa.w ^ tag) | (mca.x ^ tag) | (mca.y ^ tag) | (mca.z ^ tag) | (mca.w ^ tag)) & 0xFFFFu;) {
      msa = ld_rlx2x64(a.mod + d0); mca = ld_rlx2x64(a.mod + D_ + d0);
      if (++it > (1u << 22)) __trap();
    }
    __syncwarp();
    PT(0, wg, 2);
    const uint2 uq[4] = {make_uint2(uqa.x, uqa.y), make_uint2(uqa.z, uqa.w), make_uint2(uqb.x, uqb.y), make_uint2(uqb.z, uqb.w)};
    const uint32_t sa01 = prmt(msa.x, msa.y, 0x7632), sa23 = prmt(msa.z, msa.w, 0x7632);
    const uint32_t ca01 = hadd2(prmt(mca.x, mca.y, 0x7632), 0x3F803F80u), ca23 = hadd2(prmt(mca.z, mca.w, 0x7632), 0x3F803F80u);
    const uint32_t mm[4] = {st01.x, st01.z, st23.x, st23.z};
    const float rr[4] = {__uint_as_float(st01.y), __uint_as_float(st01.w), __uint_as_float(st23.y), __uint_as_float(st23.w)};
    uint32_t h01[4], h23[4];
#pragma unroll
    for (int r = 0; r < 4; r++) {
      const uint32_t m2 = prmt(mm[r], mm[r], 0x3232);
      uint32_t dd = hsub2(uq[r].x, m2);
      h01[r] = hadd2(hmul2(pack_bf16(bf_lo(dd) * rr[r], bf_hi(dd) * rr[r]), ca01), sa01);
      dd = hsub2(uq[r].y, m2);
      h23[r] = hadd2(hmul2(pack_bf16(bf_lo(dd) * rr[r], bf_hi(dd) * rr[r]), ca23), sa23);
    }
    const uint32_t ho = h_chunk(sm + K1_H, tid >> 1) + ((tid & 1) ? 0 : 8), uo = sm + K1_U + tid * 8;
    sts64(ho, prmt(h01[3], h01[2], 0x5410), prmt(h01[1], h01[0], 0x5410));
    sts64(ho + K1_HSZ, prmt(h01[3], h01[2], 0x7632), prmt(h01[1], h01[0], 0x7632));
    sts64(ho + 2 * K1_HSZ, prmt(h23[3], h23[2], 0x5410), prmt(h23[1], h23[0], 0x5410));
    sts64(ho + 3 * K1_HSZ, prmt(h23[3], h23[2], 0x7632), prmt(h23[1], h23[0], 0x7632));
    sts64(uo, prmt(uq[0].x, uq[1].x, 0x5410), prmt(uq[2].x, uq[3].x, 0x5410));
    sts64(uo + 4096, prmt(uq[0].x, uq[1].x, 0x7632), prmt(uq[2].x, uq[3].x, 0x7632));
    sts64(uo + 8192, prmt(uq[0].y, uq[1].y, 0x5410), prmt(uq[2].y, uq[3].y, 0x5410));
    sts64(uo + 12288, prmt(uq[0].y, uq[1].y, 0x7632), prmt(uq[2].y, uq[3].y, 0x7632));
  }
  fence_async_smem();
  __syncthreads();
  PT(0, wg, 6);
  const uint32_t H = sm + K1_H + wg * K1_HSZ, S = R + K1_S;
  float D0[32], D2[12], D3a[16], D3b[8];
  const uint32_t zb = R + ((g & 1) ? K1_Z1 : K1_Z0), zd = zb + (4 * w4 + (g >> 1) + t4) * 8, za = zb + (336 + 8 * w4 + (g >> 1) + t4) * 4;
  const uint64_t dH = mkdesc(H + 10 * 16, desc_hi(K1_CS, 128, 0)), dS = mkdesc(S, desc_hi(144, 1152, 0)), dS2 = mkdesc(S + K1_EO, desc_hi(144, 2304, 0));
  uint32_t prev;
  uint32_t sw[2][8], prev10;
#define CONV_LOAD(G)                                                                                                         \
  if ((G) < 10) {                                                                                                            \
    _Pragma("unroll") for (int i = 0; i < 4; i++) if (2 * (G) + i / 2 < 19) { const uint2 v = lds64(zd + (4 * (G) + i) * 32); sw[(G) & 1][2 * i] = v.x; sw[(G) & 1][2 * i + 1] = v.y; } \
  } else if ((G) < 16) {                                                                                                     \
    if ((G) == 10) prev10 = lds32(za);                                                                                         \
    _Pragma("unroll") for (int i = 0; i < 8; i++) sw[(G) & 1][i] = lds32(za + (8 * ((G) - 10) + i + 1) * 16);                         \
  }
#define CONV_ISSUE(G)                                                                                                        \
  {                                                                                                                          \
    uint32_t cur[8];                                                                                                         \
    _Pragma("unroll") for (int i = 0; i < 8; i++) cur[i] = sw[(G) & 1][i]; if ((G) == 10) prev = prev10;                                                            \
    wg_fence();                                                                                                              \
    if ((G) < 10) {                                                                                                          \
      _Pragma("unroll") for (int i = 0; i < 2; i++) {                                                                        \
        const int s = 2 * (G) + i;                                                                                           \
        if (s < 19) wgmma_rs_n64(D0, cur[4 * i], cur[4 * i + 1], cur[4 * i + 2], cur[4 * i + 3], dH + (uint64_t)((2 * i) * (K1_CS / 16)) - (uint64_t)(G), s > 0); \
      }                                                                                                                      \
    } else {                                                                                                                 \
      _Pragma("unroll") for (int i = 0; i < 4; i++) {                                                                        \
        const int s = 4 * ((G) - 10) + i;                                                                                    \
        const uint32_t a0 = prev, a1 = cur[2 * i], a3 = cur[2 * i + 1];                                                      \
        if (s < 4) wgmma_rs_n24(D2, a0, a1, a1, a3, dS + (K1_S5 / 16 + s * 18), s > 0);                                      \
        else if (s < 8) wgmma_rs_n16(D2, a0, a1, a1, a3, dS + (K1_S5 / 16 + s * 18), 1);                                     \
        else if (s < 12) wgmma_rs_n24(D2, a0, a1, a1, a3, dS + (K1_S3 / 16 + (s - 8) * 18), 1);                              \
        else if (s < 16) wgmma_rs_n16(D2, a0, a1, a1, a3, dS + (K1_S3 / 16 + (s - 8) * 18), 1);                              \
        else if (s < 20) wgmma_rs_n32(D3a, a0, a1, a1, a3, dS + (K1_EO / 16 + (s - 16) * 18), s > 16);                       \
        else wgmma_rs_n16(D3b, a0, a1, a1, a3, dS2 + (s - 16) * 18, s > 20);                                                 \
        prev = a3;                                                                                                           \
      }                                                                                                                      \
    }                                                                                                                        \
    wg_commit();                                                                                                             \
  }
#define CONV_GO(G) CONV_ISSUE(G) CONV_LOAD((G) + 1)
  CONV_LOAD(0)
  {
    const int cb = 8 * (w4 >> 1) + (w4 & 1);
    const int qa = 190 - (64 + 8 * (cb + 2 * t4) + g), qb = 190 - (8 * ((w4 & 1) + 2 * t4) + g);
    const bool second = (w4 >> 1) == (wg & 1);
    const uint32_t ro = S + (2 * ((lane & 7) >> 1)) * 144 + (2 * (lane >> 3) + (lane & 1)) * 16;
    uint4 ra[3], rb[3];
    float hh[24], c[22];
    uint32_t r5[4], r3[4];
    CONV_GO(0)
#pragma unroll
    for (int i = 0; i < 3; i++) ra[i] = lds128(h_chunk(H, qa - 1 + i));
    wg_wait<1>();
    CONV_GO(1)
    wg_wait<1>();
    CONV_GO(2)
    unpack_rev(ra[0], hh); unpack_rev(ra[1], hh + 8); unpack_rev(ra[2], hh + 16);
    c[4] = 0.f;
#pragma unroll
    for (int i = 4; i < 21; i++) c[i + 1] = c[i] + hh[i];
    wg_wait<1>();
    CONV_GO(3)
#pragma unroll
    for (int j = 0; j < 4; j++) {
      r5[j] = pack_bf16(c[11 + 2 * j] - c[6 + 2 * j], c[12 + 2 * j] - c[7 + 2 * j]);
      r3[j] = pack_bf16(c[14 + 2 * j] - c[11 + 2 * j], c[15 + 2 * j] - c[12 + 2 * j]);
    }
    stsm4t(ro + K1_S5 + (8 + cb) * 144, r5[0], r5[1], r5[2], r5[3]);
    stsm4t(ro + K1_S3 + (8 + cb) * 144, r3[0], r3[1], r3[2], r3[3]);
    if (second) {
#pragma unroll
      for (int i = 0; i < 3; i++) rb[i] = lds128(h_chunk(H, qb - 1 + i));
    }
    wg_wait<1>();
    CONV_GO(4)
#pragma unroll
    for (int j = 0; j < 4; j++) {
      const uint32_t s9 = pack_bf16(c[13 + 2 * j] - c[4 + 2 * j], c[14 + 2 * j] - c[5 + 2 * j]);
      const uint32_t s7 = pack_bf16(c[12 + 2 * j] - c[5 + 2 * j], c[13 + 2 * j] - c[6 + 2 * j]);
      r5[j] = (g & 1) ? s7 : s9; r3[j] = (g & 1) ? s9 : s7;
    }
    stsm4t(ro + K1_EO + cb * 144, r5[0], r5[1], r5[2], r5[3]);
    stsm4t(ro + K1_EO + 2304 + cb * 144, r3[0], r3[1], r3[2], r3[3]);
    wg_wait<1>();
    CONV_GO(5)
    if (second) {
      unpack_rev(rb[0], hh); unpack_rev(rb[1], hh + 8); unpack_rev(rb[2], hh + 16);
      c[6] = 0.f;
#pragma unroll
      for (int i = 6; i < 21; i++) c[i + 1] = c[i] + hh[i];
    }
    wg_wait<1>();
    CONV_GO(6)
    if (second) {
#pragma unroll
      for (int j = 0; j < 4; j++) {
        r5[j] = pack_bf16(c[11 + 2 * j] - c[6 + 2 * j], c[12 + 2 * j] - c[7 + 2 * j]);
        r3[j] = pack_bf16(c[14 + 2 * j] - c[11 + 2 * j], c[15 + 2 * j] - c[12 + 2 * j]);
      }
      stsm4t(ro + K1_S5 + (w4 & 1) * 144, r5[0], r5[1], r5[2], r5[3]);
      stsm4t(ro + K1_S3 + (w4 & 1) * 144, r3[0], r3[1], r3[2], r3[3]);
    }
    fence_async_smem();
    wg_wait<1>();
  }
  CONV_GO(7)
  const uint32_t hc0 = h_chunk(H, t);
  const uint4 hm = lds128(h_chunk(H, t - 1)), h0 = lds128(hc0), hp = lds128(h_chunk(H, t + 1));
  const float kv = lds32f(s_kv1024 + wg * 4);
  uint32_t graw = ld_rlx32(a.mod + 2 * D_ + d0 + wg);
  const uint32_t dskr = ldg16_nc(a.dskip + d0 + wg);
  wg_wait<1>();
  CONV_GO(8)
  bar_sync(2 + wg, 128);
  wg_wait<1>();
  CONV_GO(9)
  float f[8];
  {
    float hh[24], c[19];
    unpack_rev(hm, hh); unpack_rev(h0, hh + 8); unpack_rev(hp, hh + 16);
    c[4] = 0.f;
#pragma unroll
    for (int i = 4; i < 18; i++) c[i + 1] = c[i] + hh[i];
    wg_wait<1>();
    CONV_GO(10)
#pragma unroll
    for (int e = 0; e < 8; e++) f[e] = kv * (c[e + 11] - c[e + 4]);
  }
  float f6 = 0.f, f7 = 0.f;
  if (t == 127) { const uint32_t hw = lds32(h_chunk(H, 0) + 12); f6 = kv * bf_hi(hw); f7 = kv * (bf_hi(hw) + bf_lo(hw)); }
  const uint4 h1 = lds128(hc0 + 512);
  wg_wait<1>();
  fence_regs<32>(D0);
  {
    const uint32_t y0 = R + K1_Y0 + (72 * t4 + 8 * w4 + g) * 4;
#pragma unroll
    for (int j = 0; j < 8; j++)
#pragma unroll
      for (int e = 0; e < 2; e++) sts32f(y0 + (288 * j + 36 * e) * 4, j ? D0[4 * j + e] + D0[4 * j - 2 + e] : D0[e]);
  }
  CONV_GO(11)
  const uint32_t dk2 = dskr * 0x10001u;
  const uint32_t hd[2][4] = {{hmul2(prmt(h0.w, h0.w, 0x1032), dk2), hmul2(prmt(h0.z, h0.z, 0x1032), dk2), hmul2(prmt(h0.y, h0.y, 0x1032), dk2), hmul2(prmt(h0.x, h0.x, 0x1032), dk2)},
                             {hmul2(prmt(h1.w, h1.w, 0x1032), dk2), hmul2(prmt(h1.z, h1.z, 0x1032), dk2), hmul2(prmt(h1.y, h1.y, 0x1032), dk2), hmul2(prmt(h1.x, h1.x, 0x1032), dk2)}};
  wg_wait<1>();
  CONV_GO(12)
  const uint4 u0 = lds128(sm + K1_U + wg * 4096 + t * 16), u1 = lds128(sm + K1_U + wg * 4096 + (t + 128) * 16);
  for (uint32_t it = 0; (graw ^ tag) & 0xFFFFu;) { graw = ld_rlx32(a.mod + 2 * D_ + d0 + wg); if (++it > (1u << 22)) __trap(); }
  __syncwarp();
  wg_wait<1>();
  CONV_GO(13)
  wg_wait<1>();
  CONV_GO(14)
  wg_wait<1>();
  CONV_ISSUE(15)
  PT(0, wg, 7);
  wg_wait<0>();
  fence_regs<12>(D2); fence_regs<16>(D3a); fence_regs<8>(D3b);
  PT(0, wg, 8);
  {
    const bool odd = g & 1;
#pragma unroll
    for (int e = 0; e < 4; e++) {
      D2[e] += (odd ? D3a[8 + e] : D3a[e]) + (odd ? D3b[4 + e] : D3b[e]);
      D2[4 + e] += odd ? D3a[12 + e] : D3a[4 + e];
    }
    const uint32_t y2 = R + K1_Y2 + (136 * w4 + 8 * g + 2 * t4 + 4 * (g >> 2)) * 4;
#pragma unroll
    for (int gm = 0; gm < 3; gm++)
#pragma unroll
      for (int hf = 0; hf < 2; hf++) sts64f(y2 + (68 * hf + 544 * (2 - gm)) * 4, D2[4 * gm + 2 * hf], D2[4 * gm + 2 * hf + 1]);
  }
  {
    const uint32_t ga2 = prmt(graw, 0, 0x3232);
    const uint32_t yr = R + (8 * t + 8 * (t >> 4) + 4 * ((((t >> 2) & 3) + 1) >> 1)) * 4, yq = R + K1_Y0 + (8 * t + 8 * (t >> 3) + (t & 4)) * 4;
    bar_sync(2 + wg, 128);
    PT(0, wg, 9);
    float4 ya[2][2], yb[2][2];
#pragma unroll
    for (int hf = 0; hf < 2; hf++) {
      ya[hf][0] = lds128f(yq + 1152 * 4 * hf); ya[hf][1] = lds128f(yq + 1152 * 4 * hf + 16);
      if (hf || t >= 64) { yb[hf][0] = lds128f(yr + K1_Y2 + (1088 * hf - 544) * 4); yb[hf][1] = lds128f(yr + K1_Y2 + (1088 * hf - 544) * 4 + 16); }
      else yb[hf][0] = yb[hf][1] = make_float4(0.f, 0.f, 0.f, 0.f);
    }
    bf16* xo = a.x1T + (d0 + wg) * L_ + 8 * t;
#pragma unroll
    for (int hf = 0; hf < 2; hf++) {
      float y[8] = {ya[hf][0].x + yb[hf][0].x, ya[hf][0].y + yb[hf][0].y, ya[hf][0].z + yb[hf][0].z, ya[hf][0].w + yb[hf][0].w,
                    ya[hf][1].x + yb[hf][1].x, ya[hf][1].y + yb[hf][1].y, ya[hf][1].z + yb[hf][1].z, ya[hf][1].w + yb[hf][1].w};
      if (hf) {
#pragma unroll
        for (int e = 0; e < 8; e++) y[e] += f[e];
      } else { y[6] += f6; y[7] += f7; }
      const uint4 uv = hf ? u1 : u0;
      const uint32_t un[4] = {uv.x, uv.y, uv.z, uv.w};
      uint32_t x1[4];
#pragma unroll
      for (int j = 0; j < 4; j++) x1[j] = hadd2(un[j], hmul2(ga2, hadd2(pack_bf16(y[2 * j], y[2 * j + 1]), hd[hf][j])));
      *(uint4*)(xo + 1024 * hf) = make_uint4(x1[0], x1[1], x1[2], x1[3]);
    }
  }
  PT(0, wg, 10);
}

constexpr int KB_A = 0, KB_A2 = 114688, KB_B = KB_A2 + 3 * 16384, KB_AUG = KB_B + 4 * 14336, KB_BAR = KB_A2 + 7 * 16384, KB_GB = KB_BAR + 640, KB_SMEM = KB_GB + 256;
__host__ __device__ constexpr int kb_wofs(int p) {
  return p == 0 ? 0 : p == 1 ? KB_A2 + 61440 : p == 2 ? 28672 : p == 3 ? KB_A2 + 86528 : p == 4 ? 57344 : p == 5 ? 86016 : p == 6 ? KB_A2 : KB_A2 + 32768;
}

__device__ __forceinline__ float gelu_half(float h) {
  const float u = h * fmaf(h * h, 0.2854192648f, 1.5957691216f);
  float t; asm("tanh.approx.f32 %0, %1;" : "=f"(t) : "f"(u));
  return fmaf(h, t, h);
}
__device__ __forceinline__ float gelu_raw(float a, float k1, float k2) {
  float t; asm("tanh.approx.f32 %0, %1;" : "=f"(t) : "f"(a * fmaf(a * a, k2, k1)));
  return fmaf(a, t, a);
}
__device__ __forceinline__ void quad_stats(uint64_t pa, uint64_t pb, float nb, float n, float inv_tot, float& mean, float& var) {
  const float sa = __uint_as_float((uint32_t)pa), sb = __uint_as_float((uint32_t)pb);
  float s = sa + sb;
  s += __shfl_xor_sync(~0u, s, 1); s += __shfl_xor_sync(~0u, s, 2);
  mean = s * inv_tot;
  const float da = fmaf(sa, 1.0f / n, -mean), db = fmaf(sb, 1.0f / n, -mean);
  float q = __uint_as_float((uint32_t)(pa >> 32)) + __uint_as_float((uint32_t)(pb >> 32)) + fmaf(n * da, da, nb * db * db);
  q += __shfl_xor_sync(~0u, q, 1); q += __shfl_xor_sync(~0u, q, 2);
  var = q * inv_tot;
}
__device__ __forceinline__ void gather4(const uint2* base, int hi_ofs, uint32_t tag, uint64_t* p) {
  for (uint32_t it = 0;; it++) {
#pragma unroll
    for (int i = 0; i < 4; i++) asm volatile("ld.relaxed.gpu.global.b64 %0, [%1];" : "=l"(p[i]) : "l"(base + (i >> 1) * hi_ofs + 8 * (i & 1)) : "memory");
    if (!((((uint32_t)(p[0] >> 32) ^ tag) | ((uint32_t)(p[1] >> 32) ^ tag) | ((uint32_t)(p[2] >> 32) ^ tag) | ((uint32_t)(p[3] >> 32) ^ tag)) & 0xFFu)) break;
    if (it > (1u << 22)) __trap();
  }
  __syncwarp();
}

constexpr uint64_t kb_wtab() { uint64_t v = 0; for (int p = 0; p < 8; p++) v |= (uint64_t)(kb_wofs(p) / 1024) << (8 * p); return v; }
constexpr uint64_t KB_WOFS = kb_wtab();
struct KBArgs { const bf16* b_sp; const unsigned int* epoch; const uint8_t *wimg, *waug; uint2 *xstat, *zstat; unsigned int* zcnt; uint8_t *z2img, *pimg; const bf16* w_out; uint8_t* woimg; unsigned int* pcnt; const uint32_t* mod; unsigned int* epoch_w; };

__global__ void __cluster_dims__(2, 1, 1) __launch_bounds__(384, 1)
kb_gemm12(const __grid_constant__ CUtensorMap tm_xs, const __grid_constant__ CUtensorMap tm_wsp, const __grid_constant__ CUtensorMap tm_x1,
          const __grid_constant__ CUtensorMap tm_out, const KBArgs a) {
  extern __shared__ __align__(1024) uint8_t smem_raw[];
  const uint32_t sm = smem_u32(smem_raw);
  const int tid = threadIdx.x, warp = __shfl_sync(~0u, tid >> 5, 0), lane = tid & 31;
  const int T = (blockIdx.x >> 1) & 15, j = blockIdx.x >> 5, kap = blockIdx.x & 1, ph = 2 * j + kap;
  const int wg = warp >> 2, w4 = warp & 3, g = lane >> 2, t4 = lane & 3;
  const uint32_t fullA = sm + KB_BAR, fullB = fullA + 56, fullA2 = fullB + 112, fullB2 = fullA2 + 56, barG = fullB2 + 32, xfull = barG + 8, rdy = xfull + 8;
  const uint32_t emptyB = rdy + 64, emptyA2 = emptyB + 56, emptyB2 = emptyA2 + 56, bar1 = emptyB2 + 32, xfree = bar1 + 8, relA = xfree + 8, xdone = relA + 8, wrdy = xdone + 8, g0done = wrdy + 8, zst = g0done + 8, xf2 = zst + 8;
  const uint32_t sb = sm + KB_B;
  const int k0 = 2 * j;
  PT(1, wg, 0);
  if (lane == 0) {
#pragma unroll 1
    for (int i = warp; i < 70; i += 12) mbar_init(fullA + 8 * i, i == 63 || i == 66 ? 8 : i < 42 || i > 63 ? 1 : 2);
    asm volatile("fence.mbarrier_init.release.cluster;" ::: "memory");
  }
  __syncthreads();
  asm volatile("barrier.cluster.arrive.relaxed.aligned;" ::: "memory");
  const uint32_t tagraw = ldg32_nc(a.epoch);
  const uint32_t tag = (tagraw + 1u) & 0xFFu;
  if (wg == 2) {
    asm volatile("barrier.cluster.wait.aligned;" ::: "memory");
    if (warp == 8) {
      if (lane == 0) {
        tmap_prefetch(&tm_xs);
        mbar_expect_tx(xfull, 4096); mbar_expect_tx(xf2, 8192); mbar_expect_tx(xf2 + 8, 8192); mbar_expect_tx(xf2 + 16, 8192);
        pdl_wait();
        PT(1, 2, 1);
#pragma unroll 1
        for (int i = 0; i < 7; i++) {
          const int sl = i < 2 ? i ^ kap : i;
          const int kb = k0 + sl >= 7 ? k0 + sl - 7 : k0 + sl;
          if (i >= 3) mbar_wait(fullA + 8 * (i - 3), 0);
          mbar_expect_tx(fullA + 8 * sl, 16384);
          tma_load_2d_mc(sm + KB_A + sl * 16384 + kap * 8192, &tm_xs, T * 128 + kap * 64, kb * 64, fullA + 8 * sl, 3);
        }
        mbar_expect_tx(barG, 7168);
        bulk_load(sm + KB_AUG, a.waug + (8 + ph) * 3584, 3584, barG);
        bulk_load(sm + KB_AUG + 3584, a.waug + ph * 3584, 3584, barG);
#pragma unroll 1
        for (int i = 4; i < 14; i++) {
          const int kb = (k0 + i) % 7;
          if (i == 11) {
#pragma unroll 1
            for (int q = 0; q < 3; q++) {
              mbar_expect_tx(fullA2 + 8 * q, 16384);
              tma_load_2d(sm + KB_A2 + q * 16384, &tm_wsp, kap * 1024 + q * 64, T * 128, fullA2 + 8 * q);
            }
          }
          mbar_wait(emptyB + 8 * (i & 3), ((i >> 2) & 1) ^ 1);
          mbar_expect_tx(fullB + 8 * i, 14336);
          bulk_load(sb + (i & 3) * 14336, a.wimg + ((i >= 7 ? ph : 8 + ph) * 7 + kb) * 14336, 14336, fullB + 8 * i);
        }
        mbar_wait(relA, 0);
        PT(2, 2, 1);
        const uint8_t* zsrc = a.z2img + ((size_t)(kap * 16) * 4 + j) * 28672;
        int na = 3, sa = 3;
#pragma unroll 1
        for (int kb = 0; kb < 16; kb++) {
          const int s = kb & 3;
          if (!(kb & 1)) mbar_wait(rdy + 4 * kb, 0);
          if (kb == 0) PT(2, 2, 2);
          if (kb == 2) mbar_wait(bar1, 0);
          if (kb >= 4) mbar_wait(emptyB2 + 8 * s, ((kb >> 2) & 1) ^ 1);
          mbar_expect_tx(fullB2 + 8 * s, 28672);
          bulk_load(sm + s * 28672, zsrc + (size_t)kb * 4 * 28672 + kap * 14336, 14336, fullB2 + 8 * s);
          bulk_load(sm + s * 28672 + 14336, zsrc + (size_t)kb * 4 * 28672 + (kap ^ 1) * 14336, 14336, fullB2 + 8 * s);
#pragma unroll 1
          while (na < 16 && na < kb + 2) {
            if (na >= 7) mbar_wait(emptyA2 + 8 * sa, na >= 14);
            mbar_expect_tx(fullA2 + 8 * sa, 16384);
            tma_load_2d(sm + KB_A2 + sa * 16384, &tm_wsp, kap * 1024 + na * 64, T * 128, fullA2 + 8 * sa);
            na++; if (++sa == 7) sa = 0;
          }
        }
        mbar_wait(wrdy, 0);
#pragma unroll 1
        for (int p = 0; p < 8; p++) {
          if (p < 7) mbar_wait(emptyB2 + 8 * ((0x3321100 >> (4 * p)) & 3), 1); else mbar_wait(xdone, 0);
          mbar_expect_tx(fullB + 8 * p, 25088);
          bulk_load(sm + ((KB_WOFS >> (8 * p)) & 255) * 1024 + (p == 3 ? 512 : 0), a.woimg + (j * 8 + p) * 25088, 25088, fullB + 8 * p);
        }
        mbar_wait(g0done, 0);
        mbar_expect_tx(fullB + 64, 14336);
        tma_load_2d(sm, &tm_x1, (2 * T + kap) * 64, j * 112, fullB + 64);
      }
    } else {
      const int st = tid - 288;
      if (st == 64) {
#pragma unroll 1
        for (int i = 0, kb = k0; i < 4; i++) {
          if (i > 1) mbar_wait(fullB + 8 * (i - 2), 0);
          mbar_expect_tx(fullB + 8 * i, 14336);
          bulk_load(sb + i * 14336, a.wimg + ((8 + ph) * 7 + kb) * 14336, 14336, fullB + 8 * i);
          if (++kb == 7) kb = 0;
        }
        tmap_prefetch(&tm_wsp);
      }
      __syncwarp();
      if (blockIdx.x < 112) {
        const int f = blockIdx.x * 8 + (st & 7);
#pragma unroll 1
        for (int dc = st >> 3; dc < 56; dc += 12)
          *(uint4*)(a.woimg + ((dc / 14) * 8 + f / 112) * 25088 + (dc % 14) * 1792 + ((f % 112) >> 3) * 128 + (f & 7) * 16) = ldg128_nc(a.w_out + f * D_ + dc * 8);
      }
      bar_sync(3, 96);
      if (st == 0) asm volatile("red.release.gpu.global.add.u32 [%0], 1;" ::"l"(a.pcnt + 32 * 32) : "memory");
      if (tid == 352) {
        mbar_wait(zst, 0);
        asm volatile("red.release.gpu.global.add.u32 [%0], 1;" ::"l"(a.zcnt + (T * 4 + j) * 32) : "memory");
        PTX2(9);
        mbar_wait(xdone, 0);
        asm volatile("fence.acq_rel.gpu;" ::: "memory");
        asm volatile("red.relaxed.gpu.global.add.u32 [%0], 1;" ::"l"(a.pcnt + 2 * T * 32) : "memory");
        asm volatile("red.relaxed.gpu.global.add.u32 [%0], 1;" ::"l"(a.pcnt + (2 * T + 1) * 32) : "memory");
      }
      if (warp == 10) {
        const unsigned int* cnt = a.zcnt + ((kap * 8 + (lane & 7)) * 4 + j) * 32;
        const uint32_t target = (tagraw + 1u) * 2u;
        ld_rlx32(cnt);
        mbar_wait(relA, 0);
        uint32_t seen = 0;
        for (uint32_t it = 0; seen != 0xFFu; it++) {
          const unsigned int v = ld_rlx32(cnt);
          const uint32_t now = __ballot_sync(~0u, (int)(v - target) >= 0) & 0xFFu;
          if (it > (1u << 22)) __trap();
          if (now == 0xFFu) {
            asm volatile("fence.proxy.async.global;" ::: "memory");
            if (lane < 8 && (((now & ~seen) >> lane) & 1)) mbar_arrive(rdy + 8 * lane);
            seen = now;
          }
        }
        for (uint32_t it = 0; (int)(ld_rlx32(a.pcnt + 32 * 32) - (tagraw + 1u) * 128u) < 0; it++) if (it > (1u << 22)) __trap();
        ld_rlx32(a.pcnt + (2 * T + kap) * 32);
        pdl_wait();
        if (lane < 28) { const uint4 m = ldg128_cg(a.mod + 5 * D_ + j * 112 + 4 * lane); sts64(sm + KB_GB + lane * 8, prmt(m.x, m.y, 0x7632), prmt(m.z, m.w, 0x7632)); }
        if (lane == 0) { tmap_prefetch(&tm_x1); tmap_prefetch(&tm_out); }
        asm volatile("fence.acq_rel.gpu;" ::: "memory");
        asm volatile("fence.proxy.async.global;" ::: "memory");
        __syncwarp();
        if (lane == 0) mbar_arrive(wrdy);
      }
    }
    return;
  }

  const int r0 = wg * 64 + w4 * 16 + g;
  const uint32_t b0 = ldg16_nc(a.b_sp + T * 128 + r0) * 0x10001u, b1 = ldg16_nc(a.b_sp + T * 128 + r0 + 8) * 0x10001u;
  uint32_t z1[28];
  {
    const uint64_t da0 = mkdesc(sm + KB_A + wg * 8192, desc_hi(8192, 1024, 1)), db0 = mkdesc(sb, desc_hi(128, 1024, 0));
    const uint64_t daug = mkdesc(sm + KB_AUG, desc_hi(128, 256, 0));
    float a2[56], a1[56];
#define KB_MMA(i, kb, ACC)                                                                                                \
      mbar_wait(fullB + 8 * (i), 0);                                                                                      \
      wg_fence();                                                                                                         \
      _Pragma("unroll") for (int k = 0; k < 4; k++)                                                                       \
        wgmma_ss_n112<1, 1>(ACC, da0 + (kb) * 1024 + k * 128, db0 + ((i) & 3) * 896 + k * 16, ((kb) | k) != 0);                \
      wg_commit();
    mbar_wait(fullA + 8 * kap, 0);
    PT(1, wg, 1);
    if (ph < 7) {
      float cs[4] = {0.f, 0.f, 0.f, 0.f}, ql[4] = {0.f, 0.f, 0.f, 0.f}, qh[4] = {0.f, 0.f, 0.f, 0.f};
      const uint32_t ad = sm + KB_A + kap * 16384 + wg * 8192 + ((lane & 7) + (lane >> 4) * 8) * 128 + (((w4 * 2 + ((lane >> 3) & 1)) ^ (lane & 7)) << 4);
      uint32_t f[4][4];
#pragma unroll
      for (int ks = 0; ks < 4; ks++) ldsm4t(ad + ks * 2048, f[ks][0], f[ks][1], f[ks][2], f[ks][3]);
#pragma unroll
      for (int ks = 0; ks < 4; ks++) {
        mma16816(cs, f[ks][0], f[ks][1], f[ks][2], f[ks][3], 0x3F803F80u, 0x3F803F80u);
        mma16816(ql, f[ks][0], f[ks][1], f[ks][2], f[ks][3], f[ks][0], f[ks][2]);
        mma16816(qh, f[ks][0], f[ks][1], f[ks][2], f[ks][3], f[ks][1], f[ks][3]);
      }
      if (t4 == (g >> 1)) {
        const float q0 = fmaxf(fmaf(-cs[0], cs[0] * (1.0f / 64.f), (g & 1) ? ql[1] : ql[0]), 0.f), q1 = fmaxf(fmaf(-cs[2], cs[2] * (1.0f / 64.f), (g & 1) ? qh[3] : qh[2]), 0.f);
        uint2* o = a.xstat + (T * 8 + ph) * 128 + r0;
        st_rlx64x(o, __float_as_uint(cs[0]), (__float_as_uint(q0) & ~0xFFu) | tag);
        st_rlx64x(o + 8, __float_as_uint(cs[2]), (__float_as_uint(q1) & ~0xFFu) | tag);
      }
      __syncwarp();
    }
    PT(1, wg, 9);
    const int s1 = 3 + 2 * wg;
#define KB_Z2(kb) { mbar_wait(fullA + 8 * (kb), 0); KB_MMA(kb, kb, a2) if ((kb) >= 1) { wg_wait<1>(); if ((tid & 127) == 0) mbar_arrive(emptyB + 8 * (((kb) - 1) & 3)); } }
#pragma unroll 1
    for (int kb = 0; kb < s1; kb++) KB_Z2(kb)
    uint64_t p[4];
    const uint2* xs = a.xstat + (T * 8 + t4) * 128 + r0;
#pragma unroll
    for (int i = 0; i < 4; i++) asm volatile("ld.relaxed.gpu.global.b64 %0, [%1];" : "=l"(p[i]) : "l"(xs + (i >> 1) * (t4 == 3 ? 0 : 512) + 8 * (i & 1)) : "memory");
#pragma unroll 1
    for (int kb = s1; kb < s1 + 2; kb++) KB_Z2(kb)
    PT(1, wg, 10);
    float m0, m1, v0, v1;
    if (__any_sync(~0u, (((uint32_t)(p[0] >> 32) ^ tag) | ((uint32_t)(p[1] >> 32) ^ tag) | ((uint32_t)(p[2] >> 32) ^ tag) | ((uint32_t)(p[3] >> 32) ^ tag)) & 0xFFu))
      gather4(xs, t4 == 3 ? 0 : 512, tag, p);
    if (t4 == 3) p[2] = p[3] = 0ull;
    quad_stats(p[0], p[2], t4 == 3 ? 0.f : 64.f, 64.f, 1.0f / D_, m0, v0);
    quad_stats(p[1], p[3], t4 == 3 ? 0.f : 64.f, 64.f, 1.0f / D_, m1, v1);
    v0 = ln_den(v0); v1 = ln_den(v1);
    const uint32_t g0 = t4 == 0 ? pack_bf16(-m0, -m0) : t4 == 1 ? pack_bf16(v0, v0) : 0u;
    const uint32_t g1 = t4 == 0 ? pack_bf16(-m1, -m1) : t4 == 1 ? pack_bf16(v1, v1) : 0u;
#pragma unroll 1
    for (int kb = s1 + 2; kb < 7; kb++) KB_Z2(kb)
    mbar_wait(barG, 0);
    wg_fence();
    wgmma_rs_n112_tb(a2, g0, g1, 0u, 0u, daug, 1);
    wg_commit();
    PT(1, wg, 3);
    wg_wait<0>();
    fence_regs<56>(a2);
    if ((tid & 127) == 0) mbar_arrive(emptyB + 8 * 2);
    PT(1, wg, 2);
    const float rx = 0.5f * rcp_fast(v0), ry = 0.5f * rcp_fast(v1);
    {
      const float k1x = 1.5957691216f * rx, k2x = 0.2854192648f * rx * rx * rx, k1y = 1.5957691216f * ry, k2y = 0.2854192648f * ry * ry * ry;
      float s0 = 0.f, q0 = 0.f, s1 = 0.f, q1 = 0.f;
#pragma unroll
      for (int i = 0; i < 14; i++) {
        const float a = gelu_raw(a2[4 * i], k1x, k2x), b = gelu_raw(a2[4 * i + 1], k1x, k2x), c = gelu_raw(a2[4 * i + 2], k1y, k2y), d = gelu_raw(a2[4 * i + 3], k1y, k2y);
        a2[4 * i] = a; a2[4 * i + 1] = b; a2[4 * i + 2] = c; a2[4 * i + 3] = d;
        s0 += a + b; q0 = fmaf(a, a, fmaf(b, b, q0));
        s1 += c + d; q1 = fmaf(c, c, fmaf(d, d, q1));
      }
#pragma unroll
      for (int o = 1; o < 4; o <<= 1) { s0 += __shfl_xor_sync(~0u, s0, o); q0 += __shfl_xor_sync(~0u, q0, o); s1 += __shfl_xor_sync(~0u, s1, o); q1 += __shfl_xor_sync(~0u, q1, o); }
      const float ss = t4 ? s1 : s0, qq = t4 ? q1 : q0, rr = t4 ? ry : rx;
      const float m2 = fmaxf(fmaf(-ss, ss * (1.0f / 112.f), qq), 0.f) * rr * rr;
      if (t4 < 2) st_rlx64x(a.zstat + (T * 8 + ph) * 128 + r0 + 8 * t4, __float_as_uint(ss * rr), (__float_as_uint(m2) & ~0xFFu) | tag);
    }
    PT(1, wg, 4);
#pragma unroll 1
    for (int kb = 0; kb < 4; kb++) {
      KB_MMA(7 + kb, kb, a1)
      if (kb >= 1) { wg_wait<1>(); if ((tid & 127) == 0) mbar_arrive(emptyB + 8 * ((kb + 2) & 3)); }
    }
    gather4(a.zstat + (T * 8 + t4) * 128 + r0, 512, tag, p);
    PT(1, wg, 7);
    wg_wait<0>();
    if ((tid & 127) == 0) mbar_arrive(relA);
    quad_stats(p[0], p[2], 112.f, 112.f, 1.0f / FH_, m0, v0);
    quad_stats(p[1], p[3], 112.f, 112.f, 1.0f / FH_, m1, v1);
    {
      const float j0 = ln_rden(v0), j1 = ln_rden(v1);
      const float o0 = -bf_round(m0) * j0, o1 = -bf_round(m1) * j1, i0 = j0 * rx, i1 = j1 * ry;
      PT(1, wg, 11);
      uint8_t* dst = a.z2img + ((2 * T + wg) * 4 + j) * 28672 + kap * 14336 + (2 * w4) * 128 + lane * 4;
#pragma unroll
      for (int i = 0; i < 14; i++) {
        *(uint32_t*)(dst + i * 1024) = pack_bf16(fmaf(a2[4 * i], i0, o0), fmaf(a2[4 * i + 1], i0, o0));
        *(uint32_t*)(dst + i * 1024 + 128) = pack_bf16(fmaf(a2[4 * i + 2], i1, o1), fmaf(a2[4 * i + 3], i1, o1));
      }
    }
    PT(1, wg, 12);
    __syncwarp();
    if (lane == 0) mbar_arrive(zst);
    __syncwarp();
    PT(1, wg, 8);
#pragma unroll 1
    for (int kb = 4; kb < 7; kb++) { KB_MMA(7 + kb, kb, a1) }
    wg_fence();
    wgmma_rs_n112_tb(a1, g0, g1, 0u, 0u, daug + 224, 1);
    wg_commit();
    wg_wait<0>();
    fence_regs<56>(a1);
    if ((tid & 127) == 0) mbar_arrive(bar1);
    PT(1, wg, 5);
#pragma unroll
    for (int i = 0; i < 28; i++) { const float rr = (i & 1) ? ry : rx; z1[i] = pack_bf16(gelu_half(a1[2 * i] * rr), gelu_half(a1[2 * i + 1] * rr)); }
    PT(1, wg, 6);
  }
  float acc[112];
  const uint64_t dA = mkdesc(sm + KB_A2 + wg * 8192, desc_hi(16, 1024, 1)), dB = mkdesc(sm, desc_hi(128, 1024, 0));
  asm volatile("barrier.cluster.wait.aligned;" ::: "memory");
  int sa = 0, pa = 0;
#pragma unroll 1
  for (int kb = 0; kb < 16; kb++) {
    mbar_wait(fullA2 + 8 * sa, pa);
    mbar_wait(fullB2 + 8 * (kb & 3), (kb >> 2) & 1);
    if (kb == 0) PT(2, wg, 1);
    if (kb == 8) PT(2, wg, 2);
    wg_fence();
#pragma unroll
    for (int k = 0; k < 4; k++) wgmma_ss_n224<0, 1>(acc, dA + sa * 1024 + k * 2, dB + (kb & 3) * 1792 + k * 16, (kb | k) != 0);
    wg_commit();
    if (kb > 0) {
      wg_wait<1>();
      if ((tid & 127) == 0) {
        mbar_arrive(emptyB2 + 8 * ((kb - 1) & 3));
        if (kb <= 9) mbar_arrive(emptyA2 + 8 * (sa == 0 ? 6 : sa - 1));
        if (kb == 11) mbar_arrive_remote(mapa(xfree, kap ^ 1));
      }
    }
    if (++sa == 7) { sa = 0; pa ^= 1; }
  }
  wg_wait<0>();
  fence_regs<112>(acc);
  if ((tid & 127) == 0) mbar_arrive(emptyB2 + 24);
  PT(2, wg, 3);
  const uint32_t xb = sm + KB_A2 + 2 * 16384 + tid * 16;
  mbar_wait(xfree, 0);
  {
    const uint32_t dst = mapa(xb, kap ^ 1), rb = mapa(xfull, kap ^ 1), rb2 = mapa(xf2, kap ^ 1);
    const float* snd = acc + 56;
#pragma unroll
    for (int q = 0; q < 7; q++)
      asm volatile("st.async.shared::cluster.mbarrier::complete_tx::bytes.v4.b32 [%0], {%1,%2,%3,%4}, [%5];" ::"r"(dst + q * 4096), "r"(pack_bf16(snd[8 * q], snd[8 * q + 1])),
                   "r"(pack_bf16(snd[8 * q + 2], snd[8 * q + 3])), "r"(pack_bf16(snd[8 * q + 4], snd[8 * q + 5])), "r"(pack_bf16(snd[8 * q + 6], snd[8 * q + 7])), "r"(q ? rb2 + 8 * ((q - 1) >> 1) : rb) : "memory");
  }
  PT(2, wg, 4);
  uint4* dst = (uint4*)(a.pimg + ((2 * T + wg) * 8 + ph) * 14336) + (tid & 127);
#pragma unroll
  for (int q = 0; q < 7; q++) {
    if (q == 0) mbar_wait(xfull, 0);
    if (q & 1) mbar_wait(xf2 + 8 * (q >> 1), 0);
    if (q == 0) PT(2, wg, 5);
    const uint4 v = lds128(xb + q * 4096);
    const uint32_t w[4] = {v.x, v.y, v.z, v.w};
    uint32_t o[4];
#pragma unroll
    for (int i = 0; i < 4; i++)
      o[i] = hmul2(z1[4 * q + i], hadd2(pack_bf16(acc[8 * q + 2 * i] + bf_lo(w[i]), acc[8 * q + 2 * i + 1] + bf_hi(w[i])), (i & 1) ? b1 : b0));
    dst[q * 128] = make_uint4(o[0], o[1], o[2], o[3]);
  }
  PT(2, wg, 6);
  __syncwarp();
  if (lane == 0) mbar_arrive(xdone);
  __syncwarp();
  PT(2, wg, 7);
  {
    const unsigned int* cnt = a.pcnt + (2 * T + kap) * 32;
#pragma unroll 1
    for (int p = 0; p < 3; p++) mbar_wait(fullB + 16 * p + 8 * wg, 1);
    for (uint32_t it = 0; (int)(ld_rlx32(cnt) - (tagraw + 1u) * 8u) < 0; it++) if (it > (1u << 22)) __trap();
    __syncwarp();
    PT(3, wg, 4);
    float o3[56];
    const uint64_t dW = mkdesc(sm, desc_hi(128, 1792, 0));
    const uint4* asrc = (const uint4*)(a.pimg + ((2 * T + kap) * 8 + wg) * 14336) + (tid & 127);
    uint4 af[3][7];
#pragma unroll
    for (int p = 0; p < 3; p++)
#pragma unroll
      for (int k = 0; k < 7; k++) af[p][k] = ld_rlx2x64(asrc + p * 1792 + k * 128);
#pragma unroll
    for (int p = 0; p < 4; p++) {
      if (p == 3) mbar_wait(fullB + 48 + 8 * wg, 1);
      const uint64_t dp = dW + (wg ? kb_wofs(2 * p + 1) : kb_wofs(2 * p)) / 16;
      wg_fence();
#pragma unroll
      for (int k = 0; k < 7; k++) {
        if (p == 0 && k == 3) wg_fence();
        wgmma_rs_n112_tb(o3, af[p % 3][k].x, af[p % 3][k].y, af[p % 3][k].z, af[p % 3][k].w, dp + k * 16, (p | k) != 0);
      }
      wg_commit();
      if (p == 0) PT(3, wg, 1);
      if (p == 1) {
        wg_wait<1>();
#pragma unroll
        for (int k = 0; k < 7; k++) af[0][k] = ld_rlx2x64(asrc + 3 * 1792 + k * 128);
      }
      if (p == 2 && wg == 0) { bar_sync(1, 128); if (tid == 0) mbar_arrive(g0done); }
    }
    wg_wait<0>();
    fence_regs<56>(o3);
    PT(3, wg, 2);
    const uint32_t rb = sm + (tid & 127) * 16;
#pragma unroll
    for (int q = 0; q < 7; q++)
      sts128(rb + (wg ? kb_wofs(1) : kb_wofs(2)) + q * 2048, make_uint4(__float_as_uint(wg ? o3[8 * q] : o3[8 * q + 2]), __float_as_uint(wg ? o3[8 * q + 1] : o3[8 * q + 3]),
                                                                      __float_as_uint(wg ? o3[8 * q + 4] : o3[8 * q + 6]), __float_as_uint(wg ? o3[8 * q + 5] : o3[8 * q + 7])));
    if (blockIdx.x == 0 && tid == 128) *a.epoch_w = tagraw + 1u;
    mbar_wait(fullB + 64, 1);
    const int mj = lane >> 3;
    uint32_t x[16], gb[14];
#pragma unroll
    for (int jj = 0; jj < 4; jj++) {
      const int dr = min(4 * jj + mj, 13) * 8 + (lane & 7);
      ldsm4t(sm + dr * 128 + (((2 * w4 + wg) ^ (lane & 7)) << 4), x[4 * jj], x[4 * jj + 1], x[4 * jj + 2], x[4 * jj + 3]);
    }
#pragma unroll
    for (int i = 0; i < 14; i++) gb[i] = lds32(sm + KB_GB + (4 * i + t4) * 4);
    bar_sync(4, 256);
#pragma unroll
    for (int q = 0; q < 7; q++) {
      const float4 v = lds128f(rb + (wg ? kb_wofs(2) : kb_wofs(1)) + q * 2048);
      x[2 * q] = hadd2(x[2 * q], hmul2(gb[2 * q], pack_bf16((wg ? o3[8 * q + 2] : o3[8 * q]) + v.x, (wg ? o3[8 * q + 3] : o3[8 * q + 1]) + v.y)));
      x[2 * q + 1] = hadd2(x[2 * q + 1], hmul2(gb[2 * q + 1], pack_bf16((wg ? o3[8 * q + 6] : o3[8 * q + 4]) + v.z, (wg ? o3[8 * q + 7] : o3[8 * q + 5]) + v.w)));
    }
    const uint32_t ob = sm + 14336 + (16 * w4 + 8 * wg + (lane & 7)) * 224 + mj * 16;
#pragma unroll
    for (int jj = 0; jj < 3; jj++) stsm4(ob + jj * 64, x[4 * jj], x[4 * jj + 1], x[4 * jj + 2], x[4 * jj + 3]);
    asm volatile("stmatrix.sync.aligned.m8n8.x2.shared.b16 [%0], {%1,%2};" ::"r"(ob + 192), "r"(x[12]), "r"(x[13]) : "memory");
    fence_async_smem();
    bar_sync(4, 256);
    if (tid == 0) { tma_store_2d(&tm_out, sm + 14336, j * 112, (2 * T + kap) * 64); bulk_commit(); bulk_wait_read(); }
    PT(3, wg, 3);
  }
}

typedef CUresult (*PFN_tmEncode)(CUtensorMap*, CUtensorMapDataType, cuuint32_t, void*, const cuuint64_t*, const cuuint64_t*, const cuuint32_t*, const cuuint32_t*,
                                 CUtensorMapInterleave, CUtensorMapSwizzle, CUtensorMapL2promotion, CUtensorMapFloatOOBfill);
static CUtensorMap make_map(PFN_tmEncode enc, const void* base, uint64_t inner, uint64_t outer, uint32_t bi, uint32_t bo, CUtensorMapSwizzle sw) {
  CUtensorMap m; cuuint64_t gd[2] = {inner, outer}; cuuint64_t gs[1] = {inner * 2}; cuuint32_t bd[2] = {bi, bo}; cuuint32_t es[2] = {1, 1};
  enc(&m, CU_TENSOR_MAP_DATA_TYPE_BFLOAT16, 2, (void*)base, gd, gs, bd, es, CU_TENSOR_MAP_INTERLEAVE_NONE, sw, CU_TENSOR_MAP_L2_PROMOTION_L2_256B, CU_TENSOR_MAP_FLOAT_OOB_FILL_NONE);
  return m;
}
template <typename... KA, typename... A>
static void launch(void (*k)(KA...), int grid, int block, int smem, bool pdl, A... args) {
  cudaLaunchConfig_t cfg = {};
  cfg.gridDim = dim3(grid); cfg.blockDim = dim3(block); cfg.dynamicSmemBytes = smem; cfg.stream = cudaStreamPerThread;
  cudaLaunchAttribute at[1];
  at[0].id = cudaLaunchAttributeProgrammaticStreamSerialization; at[0].val.programmaticStreamSerializationAllowed = 1;
  cfg.attrs = at; cfg.numAttrs = pdl ? 1 : 0;
  cudaLaunchKernelEx(&cfg, k, args...);
}

extern "C" void kernel_launch(void* const* d_in, const int* in_sizes, int n_in, void* d_out, int out_size) {
  static PFN_tmEncode enc = nullptr;
  static void *p_x1T, *p_epoch, *p_kmap, *p_stat1, *p_mod, *p_wimg, *p_waug, *p_woimg, *p_uT, *p_xstat, *p_zstat, *p_zcnt, *p_z2img, *p_pimg, *p_pcnt;
  if (!enc) {
    void* p = nullptr; cudaDriverEntryPointQueryResult q;
    cudaGetDriverEntryPoint("cuTensorMapEncodeTiled", &p, cudaEnableDefault, &q);
    enc = (PFN_tmEncode)p;
    cudaGetSymbolAddress(&p_x1T, g_x1T); cudaGetSymbolAddress(&p_epoch, g_epoch); cudaGetSymbolAddress(&p_kmap, g_kmap); cudaGetSymbolAddress(&p_stat1, g_stat1);
    cudaGetSymbolAddress(&p_mod, g_mod); cudaGetSymbolAddress(&p_wimg, g_wimg); cudaGetSymbolAddress(&p_waug, g_waug); cudaGetSymbolAddress(&p_woimg, g_woimg); cudaGetSymbolAddress(&p_uT, g_uT);
    cudaGetSymbolAddress(&p_xstat, g_xstat); cudaGetSymbolAddress(&p_zstat, g_zstat); cudaGetSymbolAddress(&p_zcnt, g_zcnt); cudaGetSymbolAddress(&p_z2img, g_z2img); cudaGetSymbolAddress(&p_pimg, g_pimg); cudaGetSymbolAddress(&p_pcnt, g_pcnt);
    cudaFuncSetAttribute(k1_conv, cudaFuncAttributeMaxDynamicSharedMemorySize, K1_SMEM);
    cudaFuncSetAttribute(kb_gemm12, cudaFuncAttributeMaxDynamicSharedMemorySize, KB_SMEM);
  }
  K1Args a;
  a.u = (const bf16*)d_in[0]; a.Are = (const bf16*)d_in[1]; a.Aim = (const bf16*)d_in[2]; a.Bre = (const bf16*)d_in[3]; a.Bim = (const bf16*)d_in[4];
  a.Cre = (const bf16*)d_in[5]; a.Cim = (const bf16*)d_in[6]; a.logdt = (const bf16*)d_in[7]; a.dskip = (const bf16*)d_in[8];
  a.c = (const bf16*)d_in[14]; a.w_mod = (const bf16*)d_in[15]; a.w_in = (const bf16*)d_in[10];
  a.epoch = (const unsigned int*)p_epoch; a.kmap = (const uint32_t*)p_kmap; a.mod = (uint32_t*)p_mod; a.uT = (uint2*)p_uT; a.stat1 = (uint2*)p_stat1;
  a.x1T = (bf16*)p_x1T; a.wimg = (uint8_t*)p_wimg; a.waug = (uint8_t*)p_waug;
  const CUtensorMap tm_x1a = make_map(enc, p_x1T, L_, D_, 64, 64, CU_TENSOR_MAP_SWIZZLE_128B);
  const CUtensorMap tm_wsp = make_map(enc, d_in[11], L_, L_, 64, 128, CU_TENSOR_MAP_SWIZZLE_128B);
  const CUtensorMap tm_x1 = make_map(enc, p_x1T, L_, D_, 64, 112, CU_TENSOR_MAP_SWIZZLE_128B);
  const CUtensorMap tm_out = make_map(enc, d_out, D_, L_, 112, 64, CU_TENSOR_MAP_SWIZZLE_NONE);
  const CUtensorMap tm_wmod1 = make_map(enc, d_in[15], 6 * D_, D_, 64, 224, CU_TENSOR_MAP_SWIZZLE_128B);
  const CUtensorMap tm_win = make_map(enc, d_in[10], F_, D_, 64, 224, CU_TENSOR_MAP_SWIZZLE_128B);
  launch(k1_conv, 128, 512, K1_SMEM, false, a, tm_wmod1, tm_win);
  KBArgs b;
  b.b_sp = (const bf16*)d_in[12]; b.epoch = a.epoch; b.wimg = a.wimg; b.waug = a.waug; b.xstat = (uint2*)p_xstat; b.zstat = (uint2*)p_zstat;
  b.zcnt = (unsigned int*)p_zcnt; b.z2img = (uint8_t*)p_z2img; b.pimg = (uint8_t*)p_pimg;
  b.w_out = (const bf16*)d_in[13]; b.woimg = (uint8_t*)p_woimg; b.pcnt = (unsigned int*)p_pcnt; b.mod = a.mod; b.epoch_w = (unsigned int*)p_epoch;
  launch(kb_gemm12, 128, 384, KB_SMEM, true, tm_x1a, tm_wsp, tm_x1, tm_out, b);
}
```
